```python
import torch

def _softmax(x, axis=-1):
    return torch.softmax(x, dim=axis)
def _gelu(x):
    return torch.nn.functional.gelu(x, approximate="tanh")
def _silu(x):
    return torch.nn.functional.silu(x)
def _sigmoid(x):
    return torch.sigmoid(x)
def _layernorm(x, axis=-1, eps=1e-5):
    m = x.mean(dim=axis, keepdim=True)
    v = x.var(dim=axis, keepdim=True, unbiased=False)
    return (x - m) / torch.sqrt(v + eps)
def _scatter_add(tgt, idx, src, axis=0):
    return tgt.clone().index_add_(axis, idx, src)
def _segment_sum(src, seg, n):
    out = torch.zeros((n,) + src.shape[1:], dtype=src.dtype)
    return out.index_add_(0, seg, src)
def _pad(x, pw):
    flat = tuple(v for pair in reversed(pw) for v in pair)
    return torch.nn.functional.pad(x, flat)

kernel_name = 'gated_mix__linear_kernel_hedgehog__compressed_kv_cla__prompt'

def setup_inputs():

    _w = (lambda a: (lambda t: t.to(torch.bfloat16) if t.is_floating_point() else t)(torch.as_tensor(a)))
    def _A_setup():
        B, S, D, H = 1, 2048, 1024, 32
        Dh = D // H
        return {
            "x": _w((lambda *s: torch.randn(*s, dtype=torch.bfloat16) * 0.05)(B, S, D)),
            "wqkv": _w((lambda *s: torch.randn(*s, dtype=torch.bfloat16) * 1.6)(D, 3 * D)),
            "w_phi": _w((lambda *s: torch.randn(*s, dtype=torch.bfloat16) * 1.6)(H, Dh, Dh) * (Dh ** -0.5)),
            "wo": _w((lambda *s: torch.randn(*s, dtype=torch.bfloat16) * 0.05)(D, D)),
        }
    _A_in = _A_setup()

    def _B_setup():
        B, H, Sq, Sk, D, M = 1, 32, 2048, 2048, 128, 1024
        Dc = 4 * D
        return {
            "x": _w((lambda *s: torch.randn(*s, dtype=torch.bfloat16) * 0.05)(B, Sq, M)),
            "c_kv": _w((lambda *s: torch.randn(*s, dtype=torch.bfloat16) * 0.8)(B, Sk, Dc)),
            "w_q": _w((lambda *s: torch.randn(*s, dtype=torch.bfloat16) * 6.4)(M, H, D) * (M ** -0.5)),
            "w_uk": _w((lambda *s: torch.randn(*s, dtype=torch.bfloat16) * 6.4)(Dc, H, D) * (Dc ** -0.5)),
            "w_uv": _w((lambda *s: torch.randn(*s, dtype=torch.bfloat16) * 0.8)(Dc, H, D) * (Dc ** -0.5)),
            "w_o": _w((lambda *s: torch.randn(*s, dtype=torch.bfloat16) * 0.8)(H, D, M) * ((H * D) ** -0.5)),
        }
    _B_in = _B_setup()

    return {
        "A_x": _A_in["x"],
        "A_wqkv": _A_in["wqkv"],
        "A_w_phi": _A_in["w_phi"],
        "A_wo": _A_in["wo"],
        "B_x": _B_in["x"],
        "B_c_kv": _B_in["c_kv"],
        "B_w_q": _B_in["w_q"],
        "B_w_uk": _B_in["w_uk"],
        "B_w_uv": _B_in["w_uv"],
        "B_w_o": _B_in["w_o"],
        "gate_w": _w((lambda *s: torch.randn(*s, dtype=torch.bfloat16) * 0.05)(1024) * 16.0),
    }

def reference(A_x, A_wqkv, A_w_phi, A_wo, B_x, B_c_kv, B_w_q, B_w_uk, B_w_uv, B_w_o, gate_w):
    def _A_ref(x, wqkv, w_phi, wo):
        B, S, D = x.shape
        H = 32; Dh = D // H
        qkv = (lambda x, *d: x.permute(*d))((x @ wqkv).reshape(B, S, 3, H, Dh), 2, 0, 3, 1, 4)
        q, k, v = qkv[0], qkv[1], qkv[2]
        pq = torch.einsum("bhsd,hdf->bhsf", q, w_phi)
        pk = torch.einsum("bhsd,hdf->bhsf", k, w_phi)
        phi_q = torch.concatenate([_softmax(pq, axis=-1), _softmax(-pq, axis=-1)], axis=-1)
        phi_k = torch.concatenate([_softmax(pk, axis=-1), _softmax(-pk, axis=-1)], axis=-1)
        kv = torch.einsum("bhsf,bhsd->bhfd", phi_k, v)
        z  = torch.einsum("bhsf->bhf", phi_k)
        num = torch.einsum("bhqf,bhfd->bhqd", phi_q, kv)
        den = torch.einsum("bhqf,bhf->bhq", phi_q, z)[..., None] + 1e-6
        o = num / den
        return (lambda x, *d: x.permute(*d))(o, 0, 2, 1, 3).reshape(B, S, D) @ wo

    def _B_ref(x, c_kv, w_q, w_uk, w_uv, w_o):
        B, Sq, M = x.shape[0], x.shape[1], x.shape[2]
        Sk = c_kv.shape[1]
        H, D = w_q.shape[1], w_q.shape[2]
        q = torch.einsum("bqm,mhd->bhqd", x, w_q)
        k = torch.einsum("bkc,chd->bhkd", c_kv, w_uk)
        v = torch.einsum("bkc,chd->bhkd", c_kv, w_uv)
        scores = torch.einsum("bhqd,bhkd->bhqk", q, k) * (D ** -0.5)
        off = Sk - Sq
        qi = torch.arange(Sq)[:, None]
        kj = torch.arange(Sk)[None, :]
        cmask = kj <= (qi + off)
        scores = torch.where(cmask[None, None], scores, -1e9)
        p = _softmax(scores, axis=-1)
        ctx = torch.einsum("bhqk,bhkd->bhqd", p, v)
        return torch.einsum("bhqd,hdm->bqm", ctx, w_o)

    x = A_x
    g = _sigmoid((x * gate_w).sum(-1, keepdims=True))
    a = _A_ref(x, A_wqkv, A_w_phi, A_wo)
    b = _B_ref(x, B_c_kv, B_w_q, B_w_uk, B_w_uv, B_w_o)
    return g * a + (1 - g) * b
```

```cpp
#include <cuda_runtime.h>
#include <cuda_bf16.h>
#include <cuda.h>
#include <stdint.h>

typedef __nv_bfloat16 bf16;

__device__ __forceinline__ uint32_t smem_u32(const void* p) { return (uint32_t)__cvta_generic_to_shared(p); }
__device__ __forceinline__ void mbar_init(uint32_t bar, uint32_t count) {
  asm volatile("mbarrier.init.shared::cta.b64 [%0], %1;" :: "r"(bar), "r"(count) : "memory");
}
__device__ __forceinline__ void mbar_expect_tx(uint32_t bar, uint32_t bytes) {
  asm volatile("mbarrier.arrive.expect_tx.shared::cta.b64 _, [%0], %1;" :: "r"(bar), "r"(bytes) : "memory");
}
__device__ __forceinline__ void mbar_arrive(uint32_t bar) {
  asm volatile("mbarrier.arrive.shared::cta.b64 _, [%0];" :: "r"(bar) : "memory");
}
__device__ __forceinline__ void mbar_arrive_cluster(uint32_t bar, uint32_t cta) {
  asm volatile("{\n.reg .b32 ra;\nmapa.shared::cluster.u32 ra, %0, %1;\n"
               "mbarrier.arrive.shared::cluster.b64 _, [ra];\n}" :: "r"(bar), "r"(cta) : "memory");
}
__device__ __forceinline__ void mbar_wait(uint32_t bar, uint32_t parity) {
  asm volatile("{\n.reg .pred p;\n.reg .u32 n;\nmov.u32 n, 0;\n"
               "LAB_WAIT:\n"
               "mbarrier.try_wait.parity.shared::cta.b64 p, [%0], %1;\n"
               "@p bra LAB_DONE;\n"
               "add.u32 n, n, 1;\n"
               "setp.lt.u32 p, n, 4194304;\n"
               "@p bra LAB_WAIT;\n"
               "trap;\n"
               "LAB_DONE:\n}" :: "r"(bar), "r"(parity) : "memory");
}
__device__ __forceinline__ void flag_wait_ge(const int* p, int v) {
  asm volatile("{\n.reg .pred p;\n.reg .u32 n;\n.reg .s32 x;\nmov.u32 n, 0;\n"
               "LAB_WAIT:\n"
               "ld.acquire.gpu.global.s32 x, [%0];\n"
               "setp.ge.s32 p, x, %1;\n"
               "@p bra LAB_DONE;\n"
               "nanosleep.u32 100;\n"
               "add.u32 n, n, 1;\n"
               "setp.lt.u32 p, n, 4194304;\n"
               "@p bra LAB_WAIT;\n"
               "trap;\n"
               "LAB_DONE:\n}" :: "l"(p), "r"(v) : "memory");
}
__device__ __forceinline__ void fence_barrier_init() { asm volatile("fence.mbarrier_init.release.cluster;" ::: "memory"); }
__device__ __forceinline__ void fence_proxy_async_smem() { asm volatile("fence.proxy.async.shared::cta;" ::: "memory"); }
__device__ __forceinline__ void fence_proxy_async_all() { asm volatile("fence.proxy.async;" ::: "memory"); }
__device__ __forceinline__ void cluster_arrive() { asm volatile("barrier.cluster.arrive.release.aligned;" ::: "memory"); }
__device__ __forceinline__ void cluster_wait() { asm volatile("barrier.cluster.wait.acquire.aligned;" ::: "memory"); }
__device__ __forceinline__ uint32_t cluster_ctarank() { uint32_t r; asm volatile("mov.u32 %0, %%cluster_ctarank;" : "=r"(r)); return r; }

__device__ __forceinline__ void tma_load_2d(uint32_t dst, const CUtensorMap* m, int c0, int c1, uint32_t bar) {
  asm volatile("cp.async.bulk.tensor.2d.shared::cluster.global.mbarrier::complete_tx::bytes [%0], [%1, {%3, %4}], [%2];"
               :: "r"(dst), "l"(m), "r"(bar), "r"(c0), "r"(c1) : "memory");
}
__device__ __forceinline__ void tma_load_3d(uint32_t dst, const CUtensorMap* m, int c0, int c1, int c2, uint32_t bar) {
  asm volatile("cp.async.bulk.tensor.3d.shared::cluster.global.mbarrier::complete_tx::bytes [%0], [%1, {%3, %4, %5}], [%2];"
               :: "r"(dst), "l"(m), "r"(bar), "r"(c0), "r"(c1), "r"(c2) : "memory");
}
__device__ __forceinline__ void tma_load_3d_mc(uint32_t dst, const CUtensorMap* m, int c0, int c1, int c2, uint32_t bar, uint16_t mask) {
  asm volatile("cp.async.bulk.tensor.3d.shared::cluster.global.mbarrier::complete_tx::bytes.multicast::cluster [%0], [%1, {%3, %4, %5}], [%2], %6;"
               :: "r"(dst), "l"(m), "r"(bar), "r"(c0), "r"(c1), "r"(c2), "h"(mask) : "memory");
}
__device__ __forceinline__ void bulk_load_1d(uint32_t dst, const void* src, uint32_t bytes, uint32_t bar) {
  asm volatile("cp.async.bulk.shared::cluster.global.mbarrier::complete_tx::bytes [%0], [%1], %2, [%3];"
               :: "r"(dst), "l"(src), "r"(bytes), "r"(bar) : "memory");
}
__device__ __forceinline__ void tma_store_2d(const CUtensorMap* m, uint32_t src, int c0, int c1) {
  asm volatile("cp.async.bulk.tensor.2d.global.shared::cta.bulk_group [%0, {%2, %3}], [%1];"
               :: "l"(m), "r"(src), "r"(c0), "r"(c1) : "memory");
}
__device__ __forceinline__ void bulk_commit() { asm volatile("cp.async.bulk.commit_group;" ::: "memory"); }
template <int N> __device__ __forceinline__ void bulk_wait() { asm volatile("cp.async.bulk.wait_group %0;" :: "n"(N) : "memory"); }
__device__ __forceinline__ void prefetch_tmap(const CUtensorMap* m) { asm volatile("prefetch.tensormap [%0];" :: "l"(m) : "memory"); }

__device__ __forceinline__ void wg_fence() { asm volatile("wgmma.fence.sync.aligned;" ::: "memory"); }
__device__ __forceinline__ void wg_commit() { asm volatile("wgmma.commit_group.sync.aligned;" ::: "memory"); }
template <int N> __device__ __forceinline__ void wg_wait() { asm volatile("wgmma.wait_group.sync.aligned %0;" :: "n"(N) : "memory"); }
template <int N> __device__ __forceinline__ void reg_alloc() { asm volatile("setmaxnreg.inc.sync.aligned.u32 %0;" :: "n"(N)); }
template <int N> __device__ __forceinline__ void reg_dealloc() { asm volatile("setmaxnreg.dec.sync.aligned.u32 %0;" :: "n"(N)); }
__device__ __forceinline__ void named_bar_sync(int id, int n) { asm volatile("bar.sync %0, %1;" :: "r"(id), "r"(n) : "memory"); }
__device__ __forceinline__ void named_bar_arrive(int id, int n) { asm volatile("bar.arrive %0, %1;" :: "r"(id), "r"(n) : "memory"); }

__device__ __forceinline__ uint64_t make_desc(uint32_t addr, uint32_t lbo_bytes, uint32_t sbo_bytes, uint32_t swz) {
  return (uint64_t)((addr & 0x3FFFF) >> 4) | ((uint64_t)(lbo_bytes >> 4) << 16) | ((uint64_t)(sbo_bytes >> 4) << 32) | ((uint64_t)swz << 62);
}
__device__ __forceinline__ uint32_t pack_bf16(float lo, float hi) {
  uint32_t r; asm("cvt.rn.bf16x2.f32 %0, %1, %2;" : "=r"(r) : "f"(hi), "f"(lo)); return r;
}
__device__ __forceinline__ void stmatrix_x4(uint32_t addr, uint32_t r0, uint32_t r1, uint32_t r2, uint32_t r3) {
  asm volatile("stmatrix.sync.aligned.m8n8.x4.shared.b16 [%0], {%1, %2, %3, %4};" :: "r"(addr), "r"(r0), "r"(r1), "r"(r2), "r"(r3) : "memory");
}
__device__ __forceinline__ void st_global_v4(void* p, uint32_t a, uint32_t b, uint32_t c, uint32_t d) {
  asm volatile("st.global.v4.u32 [%0], {%1, %2, %3, %4};" :: "l"(p), "r"(a), "r"(b), "r"(c), "r"(d) : "memory");
}
__device__ __forceinline__ void red_add_v2(float* p, float a, float b) {
  asm volatile("red.global.add.v2.f32 [%0], {%1, %2};" :: "l"(p), "f"(a), "f"(b) : "memory");
}
__device__ __forceinline__ void red_add(float* p, float a) {
  asm volatile("red.global.add.f32 [%0], %1;" :: "l"(p), "f"(a) : "memory");
}
__device__ __forceinline__ float ex2(float x) { float y; asm("ex2.approx.ftz.f32 %0, %1;" : "=f"(y) : "f"(x)); return y; }
__device__ __forceinline__ float rcp_approx(float x) { float y; asm("rcp.approx.ftz.f32 %0, %1;" : "=f"(y) : "f"(x)); return y; }
__device__ __forceinline__ int opaque_tid() { int t; asm volatile("mov.u32 %0, %%tid.x;" : "=r"(t)); return t; }
template <int NR> __device__ __forceinline__ void fence_regs(float* d) {
#pragma unroll
  for (int i = 0; i < NR; i++) asm volatile("" : "+f"(d[i]) :: "memory");
}
template <int NR> __device__ __forceinline__ void fence_regs_u(uint32_t* d) {
#pragma unroll
  for (int i = 0; i < NR; i++) asm volatile("" : "+r"(d[i]) :: "memory");
}

__device__ __forceinline__ void wgmma_rs_n128_b1(float* d, const uint32_t* a, uint64_t db, int scale_d) {
  asm volatile("{\n.reg .pred p;\nsetp.ne.b32 p, %69, 0;\n"
    "wgmma.mma_async.sync.aligned.m64n128k16.f32.bf16.bf16 {%0, %1, %2, %3, %4, %5, %6, %7, %8, %9, %10, %11, %12, %13, %14, %15, %16, %17, %18, %19, %20, %21, %22, %23, %24, %25, %26, %27, %28, %29, %30, %31, %32, %33, %34, %35, %36, %37, %38, %39, %40, %41, %42, %43, %44, %45, %46, %47, %48, %49, %50, %51, %52, %53, %54, %55, %56, %57, %58, %59, %60, %61, %62, %63}, {%64, %65, %66, %67}, %68, p, 1, 1, 1;\n}\n"
    : "+f"(d[0]), "+f"(d[1]), "+f"(d[2]), "+f"(d[3]), "+f"(d[4]), "+f"(d[5]), "+f"(d[6]), "+f"(d[7]), "+f"(d[8]), "+f"(d[9]), "+f"(d[10]), "+f"(d[11]), "+f"(d[12]), "+f"(d[13]), "+f"(d[14]), "+f"(d[15]), "+f"(d[16]), "+f"(d[17]), "+f"(d[18]), "+f"(d[19]), "+f"(d[20]), "+f"(d[21]), "+f"(d[22]), "+f"(d[23]), "+f"(d[24]), "+f"(d[25]), "+f"(d[26]), "+f"(d[27]), "+f"(d[28]), "+f"(d[29]), "+f"(d[30]), "+f"(d[31]), "+f"(d[32]), "+f"(d[33]), "+f"(d[34]), "+f"(d[35]), "+f"(d[36]), "+f"(d[37]), "+f"(d[38]), "+f"(d[39]), "+f"(d[40]), "+f"(d[41]), "+f"(d[42]), "+f"(d[43]), "+f"(d[44]), "+f"(d[45]), "+f"(d[46]), "+f"(d[47]), "+f"(d[48]), "+f"(d[49]), "+f"(d[50]), "+f"(d[51]), "+f"(d[52]), "+f"(d[53]), "+f"(d[54]), "+f"(d[55]), "+f"(d[56]), "+f"(d[57]), "+f"(d[58]), "+f"(d[59]), "+f"(d[60]), "+f"(d[61]), "+f"(d[62]), "+f"(d[63])
    : "r"(a[0]), "r"(a[1]), "r"(a[2]), "r"(a[3]), "l"(db), "r"(scale_d));
}
__device__ __forceinline__ void wgmma_rs_n32_b1(float* d, const uint32_t* a, uint64_t db, int scale_d) {
  asm volatile("{\n.reg .pred p;\nsetp.ne.b32 p, %21, 0;\n"
    "wgmma.mma_async.sync.aligned.m64n32k16.f32.bf16.bf16 {%0, %1, %2, %3, %4, %5, %6, %7, %8, %9, %10, %11, %12, %13, %14, %15}, {%16, %17, %18, %19}, %20, p, 1, 1, 1;\n}\n"
    : "+f"(d[0]), "+f"(d[1]), "+f"(d[2]), "+f"(d[3]), "+f"(d[4]), "+f"(d[5]), "+f"(d[6]), "+f"(d[7]), "+f"(d[8]), "+f"(d[9]), "+f"(d[10]), "+f"(d[11]), "+f"(d[12]), "+f"(d[13]), "+f"(d[14]), "+f"(d[15])
    : "r"(a[0]), "r"(a[1]), "r"(a[2]), "r"(a[3]), "l"(db), "r"(scale_d));
}
__device__ __forceinline__ void wgmma_rs_n8_b1(float* d, const uint32_t* a, uint64_t db, int scale_d) {
  asm volatile("{\n.reg .pred p;\nsetp.ne.b32 p, %9, 0;\n"
    "wgmma.mma_async.sync.aligned.m64n8k16.f32.bf16.bf16 {%0, %1, %2, %3}, {%4, %5, %6, %7}, %8, p, 1, 1, 1;\n}\n"
    : "+f"(d[0]), "+f"(d[1]), "+f"(d[2]), "+f"(d[3])
    : "r"(a[0]), "r"(a[1]), "r"(a[2]), "r"(a[3]), "l"(db), "r"(scale_d));
}
__device__ __forceinline__ void wgmma_ss_n128_a0b0(float* d, uint64_t da, uint64_t db, int scale_d) {
  asm volatile("{\n.reg .pred p;\nsetp.ne.b32 p, %66, 0;\n"
    "wgmma.mma_async.sync.aligned.m64n128k16.f32.bf16.bf16 {%0, %1, %2, %3, %4, %5, %6, %7, %8, %9, %10, %11, %12, %13, %14, %15, %16, %17, %18, %19, %20, %21, %22, %23, %24, %25, %26, %27, %28, %29, %30, %31, %32, %33, %34, %35, %36, %37, %38, %39, %40, %41, %42, %43, %44, %45, %46, %47, %48, %49, %50, %51, %52, %53, %54, %55, %56, %57, %58, %59, %60, %61, %62, %63}, %64, %65, p, 1, 1, 0, 0;\n}\n"
    : "+f"(d[0]), "+f"(d[1]), "+f"(d[2]), "+f"(d[3]), "+f"(d[4]), "+f"(d[5]), "+f"(d[6]), "+f"(d[7]), "+f"(d[8]), "+f"(d[9]), "+f"(d[10]), "+f"(d[11]), "+f"(d[12]), "+f"(d[13]), "+f"(d[14]), "+f"(d[15]), "+f"(d[16]), "+f"(d[17]), "+f"(d[18]), "+f"(d[19]), "+f"(d[20]), "+f"(d[21]), "+f"(d[22]), "+f"(d[23]), "+f"(d[24]), "+f"(d[25]), "+f"(d[26]), "+f"(d[27]), "+f"(d[28]), "+f"(d[29]), "+f"(d[30]), "+f"(d[31]), "+f"(d[32]), "+f"(d[33]), "+f"(d[34]), "+f"(d[35]), "+f"(d[36]), "+f"(d[37]), "+f"(d[38]), "+f"(d[39]), "+f"(d[40]), "+f"(d[41]), "+f"(d[42]), "+f"(d[43]), "+f"(d[44]), "+f"(d[45]), "+f"(d[46]), "+f"(d[47]), "+f"(d[48]), "+f"(d[49]), "+f"(d[50]), "+f"(d[51]), "+f"(d[52]), "+f"(d[53]), "+f"(d[54]), "+f"(d[55]), "+f"(d[56]), "+f"(d[57]), "+f"(d[58]), "+f"(d[59]), "+f"(d[60]), "+f"(d[61]), "+f"(d[62]), "+f"(d[63])
    : "l"(da), "l"(db), "r"(scale_d));
}
__device__ __forceinline__ void wgmma_ss_n128_a0b1(float* d, uint64_t da, uint64_t db, int scale_d) {
  asm volatile("{\n.reg .pred p;\nsetp.ne.b32 p, %66, 0;\n"
    "wgmma.mma_async.sync.aligned.m64n128k16.f32.bf16.bf16 {%0, %1, %2, %3, %4, %5, %6, %7, %8, %9, %10, %11, %12, %13, %14, %15, %16, %17, %18, %19, %20, %21, %22, %23, %24, %25, %26, %27, %28, %29, %30, %31, %32, %33, %34, %35, %36, %37, %38, %39, %40, %41, %42, %43, %44, %45, %46, %47, %48, %49, %50, %51, %52, %53, %54, %55, %56, %57, %58, %59, %60, %61, %62, %63}, %64, %65, p, 1, 1, 0, 1;\n}\n"
    : "+f"(d[0]), "+f"(d[1]), "+f"(d[2]), "+f"(d[3]), "+f"(d[4]), "+f"(d[5]), "+f"(d[6]), "+f"(d[7]), "+f"(d[8]), "+f"(d[9]), "+f"(d[10]), "+f"(d[11]), "+f"(d[12]), "+f"(d[13]), "+f"(d[14]), "+f"(d[15]), "+f"(d[16]), "+f"(d[17]), "+f"(d[18]), "+f"(d[19]), "+f"(d[20]), "+f"(d[21]), "+f"(d[22]), "+f"(d[23]), "+f"(d[24]), "+f"(d[25]), "+f"(d[26]), "+f"(d[27]), "+f"(d[28]), "+f"(d[29]), "+f"(d[30]), "+f"(d[31]), "+f"(d[32]), "+f"(d[33]), "+f"(d[34]), "+f"(d[35]), "+f"(d[36]), "+f"(d[37]), "+f"(d[38]), "+f"(d[39]), "+f"(d[40]), "+f"(d[41]), "+f"(d[42]), "+f"(d[43]), "+f"(d[44]), "+f"(d[45]), "+f"(d[46]), "+f"(d[47]), "+f"(d[48]), "+f"(d[49]), "+f"(d[50]), "+f"(d[51]), "+f"(d[52]), "+f"(d[53]), "+f"(d[54]), "+f"(d[55]), "+f"(d[56]), "+f"(d[57]), "+f"(d[58]), "+f"(d[59]), "+f"(d[60]), "+f"(d[61]), "+f"(d[62]), "+f"(d[63])
    : "l"(da), "l"(db), "r"(scale_d));
}
__device__ __forceinline__ void wgmma_ss_n256_a0b1(float* d, uint64_t da, uint64_t db, int scale_d) {
  asm volatile("{\n.reg .pred p;\nsetp.ne.b32 p, %130, 0;\n"
    "wgmma.mma_async.sync.aligned.m64n256k16.f32.bf16.bf16 {%0, %1, %2, %3, %4, %5, %6, %7, %8, %9, %10, %11, %12, %13, %14, %15, %16, %17, %18, %19, %20, %21, %22, %23, %24, %25, %26, %27, %28, %29, %30, %31, %32, %33, %34, %35, %36, %37, %38, %39, %40, %41, %42, %43, %44, %45, %46, %47, %48, %49, %50, %51, %52, %53, %54, %55, %56, %57, %58, %59, %60, %61, %62, %63, %64, %65, %66, %67, %68, %69, %70, %71, %72, %73, %74, %75, %76, %77, %78, %79, %80, %81, %82, %83, %84, %85, %86, %87, %88, %89, %90, %91, %92, %93, %94, %95, %96, %97, %98, %99, %100, %101, %102, %103, %104, %105, %106, %107, %108, %109, %110, %111, %112, %113, %114, %115, %116, %117, %118, %119, %120, %121, %122, %123, %124, %125, %126, %127}, %128, %129, p, 1, 1, 0, 1;\n}\n"
    : "+f"(d[0]), "+f"(d[1]), "+f"(d[2]), "+f"(d[3]), "+f"(d[4]), "+f"(d[5]), "+f"(d[6]), "+f"(d[7]), "+f"(d[8]), "+f"(d[9]), "+f"(d[10]), "+f"(d[11]), "+f"(d[12]), "+f"(d[13]), "+f"(d[14]), "+f"(d[15]), "+f"(d[16]), "+f"(d[17]), "+f"(d[18]), "+f"(d[19]), "+f"(d[20]), "+f"(d[21]), "+f"(d[22]), "+f"(d[23]), "+f"(d[24]), "+f"(d[25]), "+f"(d[26]), "+f"(d[27]), "+f"(d[28]), "+f"(d[29]), "+f"(d[30]), "+f"(d[31]), "+f"(d[32]), "+f"(d[33]), "+f"(d[34]), "+f"(d[35]), "+f"(d[36]), "+f"(d[37]), "+f"(d[38]), "+f"(d[39]), "+f"(d[40]), "+f"(d[41]), "+f"(d[42]), "+f"(d[43]), "+f"(d[44]), "+f"(d[45]), "+f"(d[46]), "+f"(d[47]), "+f"(d[48]), "+f"(d[49]), "+f"(d[50]), "+f"(d[51]), "+f"(d[52]), "+f"(d[53]), "+f"(d[54]), "+f"(d[55]), "+f"(d[56]), "+f"(d[57]), "+f"(d[58]), "+f"(d[59]), "+f"(d[60]), "+f"(d[61]), "+f"(d[62]), "+f"(d[63]), "+f"(d[64]), "+f"(d[65]), "+f"(d[66]), "+f"(d[67]), "+f"(d[68]), "+f"(d[69]), "+f"(d[70]), "+f"(d[71]), "+f"(d[72]), "+f"(d[73]), "+f"(d[74]), "+f"(d[75]), "+f"(d[76]), "+f"(d[77]), "+f"(d[78]), "+f"(d[79]), "+f"(d[80]), "+f"(d[81]), "+f"(d[82]), "+f"(d[83]), "+f"(d[84]), "+f"(d[85]), "+f"(d[86]), "+f"(d[87]), "+f"(d[88]), "+f"(d[89]), "+f"(d[90]), "+f"(d[91]), "+f"(d[92]), "+f"(d[93]), "+f"(d[94]), "+f"(d[95]), "+f"(d[96]), "+f"(d[97]), "+f"(d[98]), "+f"(d[99]), "+f"(d[100]), "+f"(d[101]), "+f"(d[102]), "+f"(d[103]), "+f"(d[104]), "+f"(d[105]), "+f"(d[106]), "+f"(d[107]), "+f"(d[108]), "+f"(d[109]), "+f"(d[110]), "+f"(d[111]), "+f"(d[112]), "+f"(d[113]), "+f"(d[114]), "+f"(d[115]), "+f"(d[116]), "+f"(d[117]), "+f"(d[118]), "+f"(d[119]), "+f"(d[120]), "+f"(d[121]), "+f"(d[122]), "+f"(d[123]), "+f"(d[124]), "+f"(d[125]), "+f"(d[126]), "+f"(d[127])
    : "l"(da), "l"(db), "r"(scale_d));
}
__device__ __forceinline__ void wgmma_ss_n32_a1b1(float* d, uint64_t da, uint64_t db, int scale_d) {
  asm volatile("{\n.reg .pred p;\nsetp.ne.b32 p, %18, 0;\n"
    "wgmma.mma_async.sync.aligned.m64n32k16.f32.bf16.bf16 {%0, %1, %2, %3, %4, %5, %6, %7, %8, %9, %10, %11, %12, %13, %14, %15}, %16, %17, p, 1, 1, 1, 1;\n}\n"
    : "+f"(d[0]), "+f"(d[1]), "+f"(d[2]), "+f"(d[3]), "+f"(d[4]), "+f"(d[5]), "+f"(d[6]), "+f"(d[7]), "+f"(d[8]), "+f"(d[9]), "+f"(d[10]), "+f"(d[11]), "+f"(d[12]), "+f"(d[13]), "+f"(d[14]), "+f"(d[15])
    : "l"(da), "l"(db), "r"(scale_d));
}
__device__ __forceinline__ void wgmma_ss_n8_a1b1(float* d, uint64_t da, uint64_t db, int scale_d) {
  asm volatile("{\n.reg .pred p;\nsetp.ne.b32 p, %6, 0;\n"
    "wgmma.mma_async.sync.aligned.m64n8k16.f32.bf16.bf16 {%0, %1, %2, %3}, %4, %5, p, 1, 1, 1, 1;\n}\n"
    : "+f"(d[0]), "+f"(d[1]), "+f"(d[2]), "+f"(d[3])
    : "l"(da), "l"(db), "r"(scale_d));
}

constexpr int S_LEN = 2048;
constexpr int PANEL_ELEMS = S_LEN * 64;
constexpr float LOG2E = 1.4426950408889634f;

__device__ bf16 g_qkv[192 * PANEL_ELEMS];
__device__ bf16 g_a3[80 * PANEL_ELEMS];
__device__ float g_gate[S_LEN];
__device__ float4 g_kvpart[16 * 32 * 4 * 128];
__device__ float g_zpart[16 * 32 * 64];
__device__ bf16 g_kvimg[32 * 64 * 32];
__device__ bf16 g_zimg[32 * 64 * 8];
__device__ int g_cnt[16];

#define STAMP_BEGIN(k)
#define STAMP_END(k)
#define TRACE(k, slot)

constexpr int K1_MAXT = 12;
struct K1Params {
  CUtensorMap mX, mC, mWqkv, mWq, mWuk, mWuv, mWphi, mKVimg;
  uint16_t list[132][K1_MAXT];
};
enum { T_AKV = 0, T_BQ = 1, T_BK = 2, T_BV = 3, T_AQ = 4 };
constexpr int K1_STAGES = 4;
constexpr int K1_STAGE_BYTES = 49152;
constexpr int K1_SMEM = K1_STAGES * K1_STAGE_BYTES + 32768 + 1024 + 1024;

__device__ __forceinline__ void hedgehog_phi(const float* p, uint32_t* phi  ) {
  float mx0 = p[0], mn0 = p[0], mx1 = p[2], mn1 = p[2];
#pragma unroll
  for (int j = 0; j < 4; j++) {
    mx0 = fmaxf(mx0, fmaxf(p[4 * j], p[4 * j + 1])); mn0 = fminf(mn0, fminf(p[4 * j], p[4 * j + 1]));
    mx1 = fmaxf(mx1, fmaxf(p[4 * j + 2], p[4 * j + 3])); mn1 = fminf(mn1, fminf(p[4 * j + 2], p[4 * j + 3]));
  }
#pragma unroll
  for (int o = 1; o <= 2; o <<= 1) {
    mx0 = fmaxf(mx0, __shfl_xor_sync(0xffffffffu, mx0, o)); mn0 = fminf(mn0, __shfl_xor_sync(0xffffffffu, mn0, o));
    mx1 = fmaxf(mx1, __shfl_xor_sync(0xffffffffu, mx1, o)); mn1 = fminf(mn1, __shfl_xor_sync(0xffffffffu, mn1, o));
  }
  mx0 *= LOG2E; mn0 *= LOG2E; mx1 *= LOG2E; mn1 *= LOG2E;
  float ep[16], en[16];
  float sp0 = 0.f, sn0 = 0.f, sp1 = 0.f, sn1 = 0.f;
#pragma unroll
  for (int j = 0; j < 4; j++) {
#pragma unroll
    for (int e = 0; e < 2; e++) {
      ep[4 * j + e] = ex2(fmaf(p[4 * j + e], LOG2E, -mx0)); sp0 += ep[4 * j + e];
      en[4 * j + e] = ex2(fmaf(p[4 * j + e], -LOG2E, mn0)); sn0 += en[4 * j + e];
      ep[4 * j + 2 + e] = ex2(fmaf(p[4 * j + 2 + e], LOG2E, -mx1)); sp1 += ep[4 * j + 2 + e];
      en[4 * j + 2 + e] = ex2(fmaf(p[4 * j + 2 + e], -LOG2E, mn1)); sn1 += en[4 * j + 2 + e];
    }
  }
#pragma unroll
  for (int o = 1; o <= 2; o <<= 1) {
    sp0 += __shfl_xor_sync(0xffffffffu, sp0, o); sn0 += __shfl_xor_sync(0xffffffffu, sn0, o);
    sp1 += __shfl_xor_sync(0xffffffffu, sp1, o); sn1 += __shfl_xor_sync(0xffffffffu, sn1, o);
  }
  sp0 = rcp_approx(sp0); sn0 = rcp_approx(sn0); sp1 = rcp_approx(sp1); sn1 = rcp_approx(sn1);
#pragma unroll
  for (int j = 0; j < 4; j++) {
    phi[2 * j] = pack_bf16(ep[4 * j] * sp0, ep[4 * j + 1] * sp0);
    phi[2 * j + 1] = pack_bf16(ep[4 * j + 2] * sp1, ep[4 * j + 3] * sp1);
    phi[8 + 2 * j] = pack_bf16(en[4 * j] * sn0, en[4 * j + 1] * sn0);
    phi[8 + 2 * j + 1] = pack_bf16(en[4 * j + 2] * sn1, en[4 * j + 3] * sn1);
  }
}

__global__ void __launch_bounds__(384, 1) k1_proj(const __grid_constant__ K1Params P, const bf16* __restrict__ x, const bf16* __restrict__ gate_w) {
  extern __shared__ uint8_t smem_raw[];
  const uint32_t sbase = (smem_u32(smem_raw) + 1023) & ~1023u;
  const uint32_t stg = sbase + K1_STAGES * K1_STAGE_BYTES;
  const uint32_t ones = stg + 32768;
  const uint32_t bars = ones + 256;
  const int tid = threadIdx.x, warp = __shfl_sync(0xffffffffu, tid >> 5, 0), lane = tid & 31, wg = warp >> 2;
  STAMP_BEGIN(0)
  if (tid == 0) {
    for (int s = 0; s < K1_STAGES; s++) { mbar_init(bars + 8 * s, 1); mbar_init(bars + 8 * (K1_STAGES + s), 8); }
    fence_barrier_init();
  }
  if (tid < 64) asm volatile("st.shared.u32 [%0], %1;" :: "r"(ones + tid * 4), "r"(0x3F803F80u) : "memory");
  fence_proxy_async_smem();
  __syncthreads();
  const uint16_t* list = P.list[blockIdx.x];

  if (wg == 2) {
    reg_dealloc<40>();
    if (warp == 8) {
      if (lane == 0) {
        int s = 0, ph = 1;
        for (int it = 0; it < K1_MAXT; it++) {
          const int code = list[it];
          if (code == 0xFFFF) break;
          const int type = code >> 9, n = (code >> 4) & 31, m = code & 15;
          const CUtensorMap* mA = (type == T_BK || type == T_BV) ? &P.mC : &P.mX;
          const CUtensorMap* mB = type == T_BQ ? &P.mWq : type == T_BK ? &P.mWuk : type == T_BV ? &P.mWuv : &P.mWqkv;
          const int KS = (type == T_BK || type == T_BV) ? 8 : 16;
          const int p0 = type == T_AKV ? 16 + 2 * n : 4 * n, p1 = type == T_AKV ? 32 + 2 * n : 4 * n + 2;
          for (int ks = 0; ks < KS; ks++) {
            const uint32_t full = bars + 8 * s, a = sbase + s * K1_STAGE_BYTES;
            mbar_wait(bars + 8 * (K1_STAGES + s), ph);
            mbar_expect_tx(full, K1_STAGE_BYTES);
            tma_load_2d(a, mA, ks * 64, m * 128, full);
            tma_load_3d(a + 16384, mB, 0, ks * 64, p0, full);
            tma_load_3d(a + 32768, mB, 0, ks * 64, p1, full);
            if (++s == K1_STAGES) { s = 0; ph ^= 1; }
          }
          if (type == T_AKV || type == T_AQ) {
            const uint32_t full = bars + 8 * s, a = sbase + s * K1_STAGE_BYTES;
            mbar_wait(bars + 8 * (K1_STAGES + s), ph);
            if (type == T_AKV) {
              mbar_expect_tx(full, 8192);
              tma_load_2d(a, &P.mWphi, 0, n * 128, full);
            } else {
              flag_wait_ge(&g_cnt[8], 128);
              fence_proxy_async_all();
              mbar_expect_tx(full, 16384 + 32768 + 8192);
              tma_load_2d(a, &P.mWphi, 0, n * 256, full);
              tma_load_2d(a + 8192, &P.mWphi, 0, n * 256 + 128, full);
              tma_load_2d(a + 16384, &P.mKVimg, 0, n * 512, full);
              tma_load_2d(a + 32768, &P.mKVimg, 0, n * 512 + 256, full);
              bulk_load_1d(stg, g_zimg + n * 8 * 512, 8192, full);
            }
            if (++s == K1_STAGES) { s = 0; ph ^= 1; }
          }
        }
      }
    } else if (blockIdx.x < 128) {
#pragma unroll 1
      for (int r = warp - 9; r < 16; r += 3) {
        const int row = blockIdx.x * 16 + r;
        const uint4* xr = reinterpret_cast<const uint4*>(x + (size_t)row * 1024);
        const uint4* gw = reinterpret_cast<const uint4*>(gate_w);
        float acc = 0.f;
#pragma unroll 1
        for (int i = 0; i < 4; i++) {
          uint4 a = xr[lane + 32 * i], b = gw[lane + 32 * i];
          const uint32_t av[4] = {a.x, a.y, a.z, a.w}, bv[4] = {b.x, b.y, b.z, b.w};
#pragma unroll
          for (int j = 0; j < 4; j++) {
            acc = fmaf(__uint_as_float(av[j] << 16), __uint_as_float(bv[j] << 16), acc);
            acc = fmaf(__uint_as_float(av[j] & 0xffff0000u), __uint_as_float(bv[j] & 0xffff0000u), acc);
          }
        }
#pragma unroll
        for (int o = 16; o > 0; o >>= 1) acc += __shfl_xor_sync(0xffffffffu, acc, o);
        if (lane == 0) g_gate[row] = 1.0f / (1.0f + __expf(-acc));
      }
      named_bar_sync(5, 256 + 96);
      if (warp == 9 && lane == 0) { __threadfence(); atomicAdd(&g_cnt[blockIdx.x >> 4], 1); }
      const int h = blockIdx.x >> 2, w4 = blockIdx.x & 3;
      if (lane == 0) flag_wait_ge(&g_cnt[h >> 2], 16);
      __syncwarp();
#pragma unroll 1
      for (int j = warp - 9; j < 5; j += 3) {
        if (j < 4) {
          const float4* src = g_kvpart + (h * 4 + j) * 128 + w4 * 32 + lane;
          float4 a = make_float4(0.f, 0.f, 0.f, 0.f);
#pragma unroll 4
          for (int mm = 0; mm < 16; mm++) {
            const float4 v = __ldcg(src + mm * (32 * 4 * 128));
            a.x += v.x; a.y += v.y; a.z += v.z; a.w += v.w;
          }
          bf16* dst = g_kvimg + (h * 64 + w4 * 16 + (lane >> 2)) * 32 + 8 * (lane & 3) + 2 * j;
          *reinterpret_cast<uint32_t*>(dst) = pack_bf16(a.x, a.y);
          *reinterpret_cast<uint32_t*>(dst + 8 * 32) = pack_bf16(a.z, a.w);
        } else if (lane < 16) {
          float z = 0.f;
#pragma unroll 4
          for (int mm = 0; mm < 16; mm++) z += __ldcg(g_zpart + (mm * 32 + h) * 64 + w4 * 16 + lane);
          const uint32_t zp = pack_bf16(z, z);
          *reinterpret_cast<uint4*>(g_zimg + (h * 64 + w4 * 16 + lane) * 8) = make_uint4(zp, zp, zp, zp);
        }
      }
      fence_proxy_async_all();
      named_bar_sync(4, 96);
      if (warp == 9 && lane == 0) { __threadfence(); atomicAdd(&g_cnt[8], 1); }
    }
  } else {
    reg_alloc<232>();
    float acc[128];
    uint32_t pk[64];
    int s = 0, ph = 0;
    bf16* pend = nullptr;
    const int q4 = lane & 3;
    const int rloc = wg * 64 + (warp & 3) * 16 + (lane >> 2);

    auto release = [&](int st) { if (lane == 0) mbar_arrive(bars + 8 * (K1_STAGES + st)); };
    auto adv = [&]() { if (++s == K1_STAGES) { s = 0; ph ^= 1; } };
    auto kstep = [&](int first) {
      mbar_wait(bars + 8 * s, ph);
      const uint32_t a = sbase + s * K1_STAGE_BYTES;
      const uint64_t da = make_desc(a + wg * 8192, 16, 1024, 1), db = make_desc(a + 16384, 8192, 1024, 1);
      wg_fence();
#pragma unroll
      for (int k = 0; k < 4; k++) wgmma_ss_n256_a0b1(acc, da + k * 2, db + k * 128, (first && k == 0) ? 0 : 1);
      wg_commit();
    };
    auto store_part = [&](int i) {
      const int p = i >> 1, hh = i & 1;
      bf16* d = pend + (size_t)p * PANEL_ELEMS + hh * 8 * 64;
#pragma unroll
      for (int e = 0; e < 2; e++) {
        const int b = 2 * p + e;
        st_global_v4(d + e * 32, pk[(4 * b + 0) * 2 + hh], pk[(4 * b + 1) * 2 + hh], pk[(4 * b + 2) * 2 + hh], pk[(4 * b + 3) * 2 + hh]);
      }
    };

    for (int it = 0; it < K1_MAXT; it++) {
      const int code = list[it];
      if (code == 0xFFFF) break;
      const int type = code >> 9, n = (code >> 4) & 31, m = code & 15;
      const int KS = (type == T_BK || type == T_BV) ? 8 : 16;
      int prev;
      TRACE(0, 3 * it)
#pragma unroll
      for (int i = 0; i < 128; i++) asm volatile("" : "=f"(acc[i]));
      kstep(1); prev = s; adv();
      if (pend) store_part(0);
#pragma unroll
      for (int ks = 1; ks < 8; ks++) {
        kstep(0);
        if (pend) store_part(ks);
        wg_wait<1>(); release(prev); prev = s; adv();
      }
      for (int ks = 8; ks < KS; ks++) {
        kstep(0); wg_wait<1>(); release(prev); prev = s; adv();
      }
      wg_wait<0>(); release(prev);
      fence_regs<128>(acc);
      TRACE(0, 3 * it + 1)
      const size_t rowoff = (size_t)(m * 128 + rloc) * 64 + q4 * 8;
      if (type == T_BQ || type == T_BK || type == T_BV) {
#pragma unroll
        for (int i = 0; i < 64; i++) pk[i] = pack_bf16(acc[2 * i], acc[2 * i + 1]);
        pend = g_qkv + (size_t)((type - 1) * 64 + n * 4) * PANEL_ELEMS + rowoff;
      } else if (type == T_AKV) {
        pend = nullptr;
        const int otid = opaque_tid();
        const int srow = ((otid >> 5) & 3) * 16 + ((otid >> 3) & 1) * 8 + (otid & 7);
        const int scol = (otid >> 4) & 1;
        mbar_wait(bars + 8 * s, ph);
        const uint32_t ex = sbase + s * K1_STAGE_BYTES;
        const uint32_t vb = ex + 16384;
        const int trow = wg * 64 + srow;
#pragma unroll
        for (int b = 0; b < 4; b++) {
#pragma unroll
          for (int j = 0; j < 4; j += 2) {
            const int c = j + scol;
            const int r = 64 + 16 * b + 4 * j;
            stmatrix_x4(vb + b * 8192 + trow * 64 + ((c ^ ((srow >> 1) & 3)) << 4), pack_bf16(acc[r], acc[r + 1]), pack_bf16(acc[r + 2], acc[r + 3]),
                        pack_bf16(acc[r + 4], acc[r + 5]), pack_bf16(acc[r + 6], acc[r + 7]));
          }
        }
        uint32_t kf[32];
#pragma unroll
        for (int i = 0; i < 32; i++) kf[i] = pack_bf16(acc[2 * i], acc[2 * i + 1]);
#pragma unroll 1
        for (int r = 0; r < 2; r++) {
          float pf[32];
          wg_fence();
#pragma unroll
          for (int b = 0; b < 2; b++) {
            const uint64_t db = make_desc(ex + (2 * r + b) * 2048, 16, 512, 2);
            wgmma_rs_n32_b1(pf + 16 * b, kf + 8 * b, db, 0);
            wgmma_rs_n32_b1(pf + 16 * b, kf + 8 * b + 4, db + 64, 1);
          }
          wg_commit();
          wg_wait<0>();
          fence_regs<32>(pf); fence_regs_u<32>(kf);
#pragma unroll
          for (int i = 0; i < 16; i++) kf[i] = kf[16 + i];
          uint32_t phi[32];
          hedgehog_phi(pf, phi);
          hedgehog_phi(pf + 16, phi + 16);
          if (r) named_bar_sync(3, 256);
#pragma unroll
          for (int b = 0; b < 2; b++) {
#pragma unroll
            for (int j = 0; j < 8; j += 2) {
              const int c = j + scol;
              stmatrix_x4(stg + b * 16384 + trow * 128 + ((c ^ (srow & 7)) << 4), phi[16 * b + 2 * j], phi[16 * b + 2 * j + 1], phi[16 * b + 2 * j + 2], phi[16 * b + 2 * j + 3]);
            }
          }
          fence_proxy_async_smem();
          named_bar_sync(3, 256);
          float kv[16], zz[4];
          const uint64_t da = make_desc(stg + wg * 16384, 16, 1024, 1), dv = make_desc(vb + (2 * r + wg) * 8192, 16, 512, 2), d1 = make_desc(ones, 128, 128, 0);
          wg_fence();
#pragma unroll
          for (int k = 0; k < 8; k++) {
            wgmma_ss_n32_a1b1(kv, da + k * 128, dv + k * 64, k > 0);
            wgmma_ss_n8_a1b1(zz, da + k * 128, d1, k > 0);
          }
          wg_commit();
          wg_wait<0>();
          fence_regs<16>(kv); fence_regs<4>(zz);
          const int hh = m * 32 + n * 4 + 2 * r + wg;
          float4* dst = g_kvpart + hh * (4 * 128) + (otid & 127);
#pragma unroll
          for (int j = 0; j < 4; j++) dst[j * 128] = make_float4(kv[4 * j], kv[4 * j + 1], kv[4 * j + 2], kv[4 * j + 3]);
          if ((otid & 3) == 0) {
            float* zd = g_zpart + hh * 64 + ((otid >> 5) & 3) * 16 + ((otid >> 2) & 7);
            zd[0] = zz[0]; zd[8] = zz[2];
          }
        }
        named_bar_arrive(5, 256 + 96);
        named_bar_sync(3, 256);
        release(s); adv();
#pragma unroll
        for (int i = 0; i < 64; i++) asm volatile("" : "=r"(pk[i]));
      } else {
        mbar_wait(bars + 8 * s, ph);
        const uint32_t ex = sbase + s * K1_STAGE_BYTES;
        const float g0 = __ldcg(g_gate + m * 128 + rloc), g1 = __ldcg(g_gate + m * 128 + rloc + 8);
        uint32_t qf[64];
#pragma unroll
        for (int i = 0; i < 64; i++) qf[i] = pack_bf16(acc[2 * i], acc[2 * i + 1]);
        bf16* od = g_a3 + (size_t)(n * 4) * PANEL_ELEMS + rowoff;
#pragma unroll 1
        for (int r = 0; r < 4; r++) {
          float pf[32];
          wg_fence();
#pragma unroll
          for (int b = 0; b < 2; b++) {
            const uint64_t db = make_desc(ex + (2 * r + b) * 2048, 16, 512, 2);
            wgmma_rs_n32_b1(pf + 16 * b, qf + 8 * b, db, 0);
            wgmma_rs_n32_b1(pf + 16 * b, qf + 8 * b + 4, db + 64, 1);
          }
          wg_commit();
          wg_wait<0>();
          fence_regs<32>(pf); fence_regs_u<64>(qf);
#pragma unroll
          for (int i = 0; i < 48; i++) qf[i] = qf[16 + i];
          uint32_t phi[32];
          hedgehog_phi(pf, phi);
          hedgehog_phi(pf + 16, phi + 16);
          float num[32], den[8];
          wg_fence();
#pragma unroll
          for (int b = 0; b < 2; b++) {
            const uint64_t dk = make_desc(ex + 16384 + (2 * r + b) * 4096, 16, 512, 2), dz = make_desc(stg + (2 * r + b) * 1024, 128, 128, 0);
#pragma unroll
            for (int k = 0; k < 4; k++) {
              wgmma_rs_n32_b1(num + 16 * b, phi + 16 * b + 4 * k, dk + k * 64, k > 0);
              wgmma_rs_n8_b1(den + 4 * b, phi + 16 * b + 4 * k, dz + k * 16, k > 0);
            }
          }
          wg_commit();
          wg_wait<0>();
          fence_regs<32>(num); fence_regs<8>(den);
#pragma unroll
          for (int b = 0; b < 2; b++) {
            const float s0 = __fdividef(g0, den[4 * b] + 1e-6f), s1 = __fdividef(g1, den[4 * b + 2] + 1e-6f);
            const float* nm = num + 16 * b;
            st_global_v4(od + b * 32, pack_bf16(nm[0] * s0, nm[1] * s0), pack_bf16(nm[4] * s0, nm[5] * s0),
                         pack_bf16(nm[8] * s0, nm[9] * s0), pack_bf16(nm[12] * s0, nm[13] * s0));
            st_global_v4(od + b * 32 + 8 * 64, pack_bf16(nm[2] * s1, nm[3] * s1), pack_bf16(nm[6] * s1, nm[7] * s1),
                         pack_bf16(nm[10] * s1, nm[11] * s1), pack_bf16(nm[14] * s1, nm[15] * s1));
          }
          od += PANEL_ELEMS;
        }
        release(s); adv();
        pend = nullptr;
#pragma unroll
        for (int i = 0; i < 64; i++) asm volatile("" : "=r"(pk[i]));
      }
      TRACE(0, 3 * it + 2)
    }
    if (pend) {
#pragma unroll
      for (int i = 0; i < 8; i++) store_part(i);
    }
    STAMP_END(0)
  }
}

constexpr int K2_MAXI = 12;
struct K2Params {
  CUtensorMap mQKV;
  uint16_t list[132][K2_MAXI];
};
constexpr int K2_KST = 3, K2_VST = 2;
constexpr int K2_SMEM = (2 + K2_KST + K2_VST) * 32768 + 1024 + 256;
constexpr float SM_SCALE = 0.08838834764831845f * LOG2E;

__global__ void __launch_bounds__(384, 1) k2_attn(const __grid_constant__ K2Params P) {
  extern __shared__ uint8_t smem_raw[];
  const uint32_t sbase = (smem_u32(smem_raw) + 1023) & ~1023u;
  const uint32_t sQ = sbase, sK = sQ + 2 * 32768, sV = sK + K2_KST * 32768;
  const uint32_t bars = sV + K2_VST * 32768;
  const uint32_t qfull = bars, qempty = bars + 16, kfull = bars + 32, kempty = bars + 64, vfull = bars + 96, vempty = bars + 128;
  const int tid = threadIdx.x, warp = __shfl_sync(0xffffffffu, tid >> 5, 0), lane = tid & 31, wg = warp >> 2;
  STAMP_BEGIN(1)
  if (tid == 0) {
    for (int s = 0; s < 2; s++) { mbar_init(qfull + 8 * s, 1); mbar_init(qempty + 8 * s, 8); }
    for (int s = 0; s < K2_KST; s++) { mbar_init(kfull + 8 * s, 1); mbar_init(kempty + 8 * s, 8); }
    for (int s = 0; s < K2_VST; s++) { mbar_init(vfull + 8 * s, 1); mbar_init(vempty + 8 * s, 8); }
    fence_barrier_init();
    if (blockIdx.x == 0) { for (int i = 0; i < 9; i++) g_cnt[i] = 0; }
  }
  __syncthreads();
  const uint16_t* list = P.list[blockIdx.x];

  if (wg == 2) {
    reg_dealloc<24>();
    if (lane == 0 && warp < 11) {
      const int which = warp - 8;
      const int nst = which == 0 ? K2_KST : 2;
      const uint32_t buf = which == 0 ? sK : which == 1 ? sV : sQ;
      const uint32_t fullb = which == 0 ? kfull : which == 1 ? vfull : qfull;
      const uint32_t emptyb = which == 0 ? kempty : which == 1 ? vempty : qempty;
      const int pbase = which == 0 ? 64 : which == 1 ? 128 : 0;
      int s = 0, ph = 1;
      for (int it = 0; it < K2_MAXI; it++) {
        const int code = list[it];
        if (code == 0xFFFF) break;
        const int h = code >> 4, qt = code & 15;
        const int jend = which == 2 ? qt : 0;
        for (int j = qt; j >= jend; j--) {
          mbar_wait(emptyb + 8 * s, ph);
          mbar_expect_tx(fullb + 8 * s, 32768);
          tma_load_3d(buf + s * 32768, &P.mQKV, 0, j * 128, pbase + 2 * h, fullb + 8 * s);
          if (++s == nst) { s = 0; ph ^= 1; }
        }
      }
    }
  } else {
    reg_alloc<240>();
    float O[64], S[64];
    uint32_t Pr[32];
    float m0, m1, l0, l1, al0 = 1.f, al1 = 1.f;
    int ks = 0, kph = 0, vs = 0, vph = 0, qs = 0, qph = 0;
    const int q4 = lane & 3;
    const int rloc = wg * 64 + (warp & 3) * 16 + (lane >> 2);
#pragma unroll
    for (int i = 0; i < 64; i++) O[i] = 0.f;

    auto issue_qk = [&](int qbuf) {
      mbar_wait(kfull + 8 * ks, kph);
      const uint64_t dq = make_desc(sQ + qbuf * 32768 + wg * 8192, 16, 1024, 1), dk = make_desc(sK + ks * 32768, 16, 1024, 1);
      wg_fence();
#pragma unroll
      for (int k = 0; k < 8; k++) wgmma_ss_n128_a0b0(S, dq + (k >> 2) * 1024 + (k & 3) * 2, dk + (k >> 2) * 1024 + (k & 3) * 2, k > 0);
      wg_commit();
    };
    auto issue_pv = [&](int accumulate) {
      mbar_wait(vfull + 8 * vs, vph);
      const uint64_t dv = make_desc(sV + vs * 32768, 16384, 1024, 1);
      wg_fence();
#pragma unroll
      for (int k = 0; k < 8; k++) wgmma_rs_n128_b1(O, Pr + 4 * k, dv + k * 128, (k > 0) ? 1 : accumulate);
      wg_commit();
    };
    auto release_k = [&]() { if (lane == 0) mbar_arrive(kempty + 8 * ks); if (++ks == K2_KST) { ks = 0; kph ^= 1; } };
    auto release_k_dep = [&]() {
      const uint32_t dep = (l0 + l1 < 0.f) ? 8u : 0u;
      if (lane == 0) mbar_arrive(kempty + 8 * ks + dep);
      if (++ks == K2_KST) { ks = 0; kph ^= 1; }
    };
    auto release_v = [&]() { if (lane == 0) mbar_arrive(vempty + 8 * vs); if (++vs == K2_VST) { vs = 0; vph ^= 1; } };
    auto rescale_o = [&]() {
#pragma unroll
      for (int j = 0; j < 16; j++) { O[4 * j] *= al0; O[4 * j + 1] *= al0; O[4 * j + 2] *= al1; O[4 * j + 3] *= al1; }
    };
    auto pack_p = [&]() {
#pragma unroll
      for (int i = 0; i < 32; i++) Pr[i] = pack_bf16(S[2 * i], S[2 * i + 1]);
    };
    auto softmax = [&](bool first) {
      if (first) {
#pragma unroll
        for (int j = 0; j < 16; j++) {
          const int c = 8 * j + 2 * q4;
          if (c > rloc) S[4 * j] = -INFINITY;
          if (c + 1 > rloc) S[4 * j + 1] = -INFINITY;
          if (c > rloc + 8) S[4 * j + 2] = -INFINITY;
          if (c + 1 > rloc + 8) S[4 * j + 3] = -INFINITY;
        }
      }
      float x0 = fmaxf(S[0], S[1]), x1 = fmaxf(S[2], S[3]);
#pragma unroll
      for (int j = 1; j < 16; j++) { x0 = fmaxf(x0, fmaxf(S[4 * j], S[4 * j + 1])); x1 = fmaxf(x1, fmaxf(S[4 * j + 2], S[4 * j + 3])); }
      x0 = fmaxf(x0, __shfl_xor_sync(0xffffffffu, x0, 1)); x1 = fmaxf(x1, __shfl_xor_sync(0xffffffffu, x1, 1));
      x0 = fmaxf(x0, __shfl_xor_sync(0xffffffffu, x0, 2)); x1 = fmaxf(x1, __shfl_xor_sync(0xffffffffu, x1, 2));
      if (!first) {
        x0 = fmaxf(x0, m0); x1 = fmaxf(x1, m1);
        al0 = ex2((m0 - x0) * SM_SCALE); al1 = ex2((m1 - x1) * SM_SCALE);
      }
      m0 = x0; m1 = x1;
      const float c0 = x0 * SM_SCALE, c1 = x1 * SM_SCALE;
      float s0 = 0.f, s1 = 0.f;
#pragma unroll
      for (int j = 0; j < 16; j++) {
        S[4 * j] = ex2(fmaf(S[4 * j], SM_SCALE, -c0)); S[4 * j + 1] = ex2(fmaf(S[4 * j + 1], SM_SCALE, -c0));
        S[4 * j + 2] = ex2(fmaf(S[4 * j + 2], SM_SCALE, -c1)); S[4 * j + 3] = ex2(fmaf(S[4 * j + 3], SM_SCALE, -c1));
        s0 += S[4 * j] + S[4 * j + 1]; s1 += S[4 * j + 2] + S[4 * j + 3];
      }
      if (first) { l0 = s0; l1 = s1; } else { l0 = fmaf(l0, al0, s0); l1 = fmaf(l1, al1, s1); }
      fence_regs<64>(S);
      asm volatile("" : "+f"(l0), "+f"(l1) :: "memory");
    };

    int code = list[0];
    if (code != 0xFFFF) {
      if (wg == 1) named_bar_arrive(1, 256);
      mbar_wait(qfull, 0);
      issue_qk(0);
      wg_wait<0>(); fence_regs<64>(S);
      release_k();
      if ((code & 15) == 0) { if (lane == 0) mbar_arrive(qempty); }
      softmax(true);
      pack_p();
      for (int it = 0; it < K2_MAXI; it++) {
        const int h = code >> 4, qt = code & 15;
        TRACE(1, it)
        const int next = it + 1 < K2_MAXI ? list[it + 1] : 0xFFFF;
        for (int t = 0; t < qt; t++) {
          named_bar_sync(1 + wg, 256);
          issue_qk(qs);
          rescale_o();
          issue_pv(t > 0);
          named_bar_arrive(2 - wg, 256);
          wg_wait<1>(); fence_regs<64>(S);
          if (t == qt - 1) { if (lane == 0) mbar_arrive(qempty + 8 * qs); }
          softmax(false);
          release_k_dep();
          wg_wait<0>(); fence_regs<64>(O); fence_regs_u<32>(Pr);
          release_v();
          pack_p();
        }
        const float g0 = __ldg(g_gate + qt * 128 + rloc), g1 = __ldg(g_gate + qt * 128 + rloc + 8);
        float lf0 = l0, lf1 = l1;
        lf0 += __shfl_xor_sync(0xffffffffu, lf0, 1); lf1 += __shfl_xor_sync(0xffffffffu, lf1, 1);
        lf0 += __shfl_xor_sync(0xffffffffu, lf0, 2); lf1 += __shfl_xor_sync(0xffffffffu, lf1, 2);
        const float f0 = __fdividef(1.0f - g0, lf0), f1 = __fdividef(1.0f - g1, lf1);
        qs ^= 1; if (qs == 0) qph ^= 1;
        named_bar_sync(1 + wg, 256);
        if (next != 0xFFFF) {
          mbar_wait(qfull + 8 * qs, qph);
          issue_qk(qs);
          rescale_o();
          issue_pv(qt > 0);
          named_bar_arrive(2 - wg, 256);
          wg_wait<1>(); fence_regs<64>(S);
          if ((next & 15) == 0) { if (lane == 0) mbar_arrive(qempty + 8 * qs); }
          softmax(true);
          release_k_dep();
          wg_wait<0>(); fence_regs<64>(O); fence_regs_u<32>(Pr);
          release_v();
          pack_p();
        } else {
          rescale_o();
          issue_pv(qt > 0);
          if (wg == 0) named_bar_arrive(2 - wg, 256);
          wg_wait<0>(); fence_regs<64>(O);
        }
        bf16* dst = g_a3 + (size_t)(16 + 2 * h) * PANEL_ELEMS + (size_t)(qt * 128 + rloc) * 64 + q4 * 8;
#pragma unroll
        for (int b = 0; b < 4; b++) {
          bf16* d = dst + (size_t)(b >> 1) * PANEL_ELEMS + (b & 1) * 32;
          st_global_v4(d, pack_bf16(O[16 * b] * f0, O[16 * b + 1] * f0), pack_bf16(O[16 * b + 4] * f0, O[16 * b + 5] * f0),
                       pack_bf16(O[16 * b + 8] * f0, O[16 * b + 9] * f0), pack_bf16(O[16 * b + 12] * f0, O[16 * b + 13] * f0));
          st_global_v4(d + 8 * 64, pack_bf16(O[16 * b + 2] * f1, O[16 * b + 3] * f1), pack_bf16(O[16 * b + 6] * f1, O[16 * b + 7] * f1),
                       pack_bf16(O[16 * b + 10] * f1, O[16 * b + 11] * f1), pack_bf16(O[16 * b + 14] * f1, O[16 * b + 15] * f1));
        }
        if (next == 0xFFFF) { TRACE(1, it + 1) break; }
        code = next;
      }
    }
    STAMP_END(1)
  }
}

struct K3Params { CUtensorMap mA3, mWo, mWo2, mOut; };
constexpr int K3_STAGES = 6;
constexpr int K3_SMEM = K3_STAGES * 32768 + 1024 + 256;

__global__ void __cluster_dims__(2, 1, 1) __launch_bounds__(384, 1) k3_out(const __grid_constant__ K3Params P) {
  extern __shared__ uint8_t smem_raw[];
  const uint32_t sbase = (smem_u32(smem_raw) + 1023) & ~1023u;
  const uint32_t bars = sbase + K3_STAGES * 32768;
  const int tid = threadIdx.x, warp = __shfl_sync(0xffffffffu, tid >> 5, 0), lane = tid & 31, wg = warp >> 2;
  const uint32_t rank = cluster_ctarank();
  STAMP_BEGIN(2)
  if (tid == 0) {
    for (int s = 0; s < K3_STAGES; s++) { mbar_init(bars + 8 * s, 1); mbar_init(bars + 8 * (K3_STAGES + s), 16); }
    fence_barrier_init();
  }
  __syncthreads();
  cluster_arrive(); cluster_wait();
  const int cid = blockIdx.x >> 1;
  const int m = (cid & 7) * 2 + rank, n = cid >> 3;
  constexpr int KS = 80;
  if (wg == 2) {
    reg_dealloc<40>();
    if (warp == 8 && lane == 0) {
      int s = 0, ph = 1;
      for (int ks = 0; ks < KS; ks++) {
        const uint32_t full = bars + 8 * s, a = sbase + s * 32768;
        mbar_wait(bars + 8 * (K3_STAGES + s), ph);
        mbar_expect_tx(full, 32768);
        tma_load_3d(a, &P.mA3, 0, m * 128, ks, full);
        if (ks < 16) tma_load_3d_mc(a + 16384 + rank * 8192, &P.mWo, 0, ks * 64, n * 2 + rank, full, 3);
        else tma_load_3d_mc(a + 16384 + rank * 8192, &P.mWo2, 0, (ks - 16) * 64, n * 2 + rank, full, 3);
        if (++s == K3_STAGES) { s = 0; ph ^= 1; }
      }
    }
    cluster_arrive(); cluster_wait();
  } else {
    reg_alloc<232>();
    float acc[64];
    int s = 0, ph = 0, prev = 0;
    for (int ks = 0; ks < KS; ks++) {
      mbar_wait(bars + 8 * s, ph);
      const uint32_t a = sbase + s * 32768;
      const uint64_t da = make_desc(a + wg * 8192, 16, 1024, 1), db = make_desc(a + 16384, 8192, 1024, 1);
      wg_fence();
#pragma unroll
      for (int k = 0; k < 4; k++) wgmma_ss_n128_a0b1(acc, da + k * 2, db + k * 128, (ks == 0 && k == 0) ? 0 : 1);
      wg_commit();
      wg_wait<1>();
      if (ks > 0 && lane == 0) { mbar_arrive_cluster(bars + 8 * (K3_STAGES + prev), 0); mbar_arrive_cluster(bars + 8 * (K3_STAGES + prev), 1); }
      prev = s;
      if (++s == K3_STAGES) { s = 0; ph ^= 1; }
    }
    wg_wait<0>();
    fence_regs<64>(acc);
    named_bar_sync(3, 256);
    const uint32_t mystg = sbase + wg * 16384;
    const int srow = (warp & 3) * 16 + ((lane >> 3) & 1) * 8 + (lane & 7);
    const int scol = lane >> 4;
#pragma unroll
    for (int j = 0; j < 16; j += 2) {
      const int p = j >> 3, c = (j & 7) + scol;
      stmatrix_x4(mystg + p * 8192 + srow * 128 + ((c ^ (srow & 7)) << 4),
                  pack_bf16(acc[4 * j], acc[4 * j + 1]), pack_bf16(acc[4 * j + 2], acc[4 * j + 3]),
                  pack_bf16(acc[4 * j + 4], acc[4 * j + 5]), pack_bf16(acc[4 * j + 6], acc[4 * j + 7]));
    }
    fence_proxy_async_smem();
    named_bar_sync(1 + wg, 128);
    if ((tid & 127) == 0) {
      tma_store_2d(&P.mOut, mystg, n * 128, m * 128 + wg * 64);
      tma_store_2d(&P.mOut, mystg + 8192, n * 128 + 64, m * 128 + wg * 64);
      bulk_commit();
      bulk_wait<0>();
    }
    STAMP_END(2)
    cluster_arrive(); cluster_wait();
  }
}

typedef CUresult (*PFN_encodeTiled)(CUtensorMap*, CUtensorMapDataType, cuuint32_t, void*, const cuuint64_t*, const cuuint64_t*,
                                    const cuuint32_t*, const cuuint32_t*, CUtensorMapInterleave, CUtensorMapSwizzle,
                                    CUtensorMapL2promotion, CUtensorMapFloatOOBfill);
static PFN_encodeTiled g_encode = nullptr;
static void make_map(CUtensorMap* m, const void* ptr, int rank, uint64_t d0, uint64_t d1, uint64_t d2, uint64_t s1, uint64_t s2,
                     uint32_t b0, uint32_t b1, uint32_t b2, CUtensorMapSwizzle swz) {
  cuuint64_t d[3] = {d0, d1, d2}, s[2] = {s1, s2};
  cuuint32_t b[3] = {b0, b1, b2}, es[3] = {1, 1, 1};
  g_encode(m, CU_TENSOR_MAP_DATA_TYPE_BFLOAT16, rank, (void*)ptr, d, s, b, es, CU_TENSOR_MAP_INTERLEAVE_NONE, swz,
           CU_TENSOR_MAP_L2_PROMOTION_L2_256B, CU_TENSOR_MAP_FLOAT_OOB_FILL_NONE);
}

static void list_schedule(const uint16_t* codes, const float* cost, int njobs, int nb, int maxper, uint16_t* lists) {
  float load[132]; int cnt[132];
  for (int i = 0; i < nb; i++) { load[i] = 0.f; cnt[i] = 0; }
  for (int i = 0; i < 132 * maxper; i++) lists[i] = 0xFFFF;
  for (int j = 0; j < njobs; j++) {
    int best = -1;
    for (int i = 0; i < nb; i++) if (cnt[i] < maxper - 1 && (best < 0 || load[i] < load[best] - 1e-4f)) best = i;
    lists[best * maxper + cnt[best]++] = codes[j];
    load[best] += cost[j];
  }
}

static K1Params g_p1;
static K2Params g_p2;
static K3Params g_p3;
static const void* g_last_in[11];
static void* g_last_out = nullptr;
static bool g_attr_done = false;

extern "C" void kernel_launch(void* const* d_in, const int* in_sizes, int n_in, void* d_out, int out_size) {
  const bf16* x = (const bf16*)d_in[0];
  const bf16* wqkv = (const bf16*)d_in[1];
  const bf16* wphi = (const bf16*)d_in[2];
  const bf16* wo = (const bf16*)d_in[3];
  const bf16* ckv = (const bf16*)d_in[5];
  const bf16* wq = (const bf16*)d_in[6];
  const bf16* wuk = (const bf16*)d_in[7];
  const bf16* wuv = (const bf16*)d_in[8];
  const bf16* wo2 = (const bf16*)d_in[9];
  const bf16* gate_w = (const bf16*)d_in[10];

  bool same = g_attr_done && g_last_out == d_out;
  for (int i = 0; i < 11 && same; i++) same = g_last_in[i] == d_in[i];
  if (!same) {
    if (!g_encode) {
      cudaDriverEntryPointQueryResult qr; void* p = nullptr;
      cudaGetDriverEntryPoint("cuTensorMapEncodeTiled", &p, cudaEnableDefault, &qr);
      g_encode = (PFN_encodeTiled)p;
    }
    void *p_qkv, *p_a3, *p_kvimg;
    cudaGetSymbolAddress(&p_qkv, g_qkv); cudaGetSymbolAddress(&p_a3, g_a3); cudaGetSymbolAddress(&p_kvimg, g_kvimg);
    const CUtensorMapSwizzle S128 = CU_TENSOR_MAP_SWIZZLE_128B, S64 = CU_TENSOR_MAP_SWIZZLE_64B;
    make_map(&g_p1.mX, x, 2, 1024, 2048, 1, 2048, 0, 64, 128, 1, S128);
    make_map(&g_p1.mC, ckv, 2, 512, 2048, 1, 1024, 0, 64, 128, 1, S128);
    make_map(&g_p1.mWqkv, wqkv, 3, 64, 1024, 48, 3072 * 2, 128, 64, 64, 2, S128);
    make_map(&g_p1.mWq, wq, 3, 64, 1024, 64, 4096 * 2, 128, 64, 64, 2, S128);
    make_map(&g_p1.mWuk, wuk, 3, 64, 512, 64, 4096 * 2, 128, 64, 64, 2, S128);
    make_map(&g_p1.mWuv, wuv, 3, 64, 512, 64, 4096 * 2, 128, 64, 64, 2, S128);
    make_map(&g_p1.mWphi, wphi, 2, 32, 1024, 1, 64, 0, 32, 128, 1, S64);
    make_map(&g_p1.mKVimg, p_kvimg, 2, 32, 2048, 1, 64, 0, 32, 256, 1, S64);
    make_map(&g_p2.mQKV, p_qkv, 3, 64, 2048, 192, 128, (uint64_t)PANEL_ELEMS * 2, 64, 128, 2, S128);
    make_map(&g_p3.mA3, p_a3, 3, 64, 2048, 80, 128, (uint64_t)PANEL_ELEMS * 2, 64, 128, 1, S128);
    make_map(&g_p3.mWo, wo, 3, 64, 1024, 16, 1024 * 2, 128, 64, 64, 1, S128);
    make_map(&g_p3.mWo2, wo2, 3, 64, 4096, 16, 1024 * 2, 128, 64, 64, 1, S128);
    make_map(&g_p3.mOut, d_out, 2, 1024, 2048, 1, 2048, 0, 64, 64, 1, S128);
    {
      static uint16_t codes[960]; static float cost[960]; int nj = 0;
      auto add = [&](int type, int n, float c) { for (int m = 0; m < 16; m++) { codes[nj] = (uint16_t)((type << 9) | (n << 4) | m); cost[nj++] = c; } };
      for (int n = 0; n < 8; n++) add(T_AKV, n, 19.0f);
      for (int n = 0; n < 16; n++) {
        if (n == 10) for (int a = 0; a < 4; a++) add(T_AQ, a, 21.5f);
        if (n < 14) { add(T_BQ, n, 16.5f); add(T_BK, n, 8.5f); add(T_BV, n, 8.5f); }
        else if (n == 14) { add(T_BQ, 14, 16.5f); add(T_BQ, 15, 16.5f); add(T_BK, 14, 8.5f); add(T_BV, 14, 8.5f); }
        else { add(T_BK, n, 8.5f); add(T_BV, n, 8.5f); }
      }
      list_schedule(codes, cost, nj, 132, K1_MAXT, &g_p1.list[0][0]);
    }
    {
      static uint16_t codes[512]; static float cost[512]; int nj = 0;
      for (int hg = 3; hg >= 0; hg--)
        for (int qt = 15; qt >= 0; qt--)
          for (int h = hg * 8; h < hg * 8 + 8; h++) { codes[nj] = (uint16_t)((h << 4) | qt); cost[nj++] = qt + 1 + 0.15f; }
      list_schedule(codes, cost, nj, 132, K2_MAXI, &g_p2.list[0][0]);
    }
    cudaFuncSetAttribute(k1_proj, cudaFuncAttributeMaxDynamicSharedMemorySize, K1_SMEM);
    cudaFuncSetAttribute(k2_attn, cudaFuncAttributeMaxDynamicSharedMemorySize, K2_SMEM);
    cudaFuncSetAttribute(k3_out, cudaFuncAttributeMaxDynamicSharedMemorySize, K3_SMEM);
    for (int i = 0; i < 11; i++) g_last_in[i] = d_in[i];
    g_last_out = d_out;
    g_attr_done = true;
  }
  k1_proj<<<132, 384, K1_SMEM>>>(g_p1, x, gate_w);
  k2_attn<<<132, 384, K2_SMEM>>>(g_p2);
  k3_out<<<128, 384, K3_SMEM>>>(g_p3);
}
```

```cpp
#include <cuda_runtime.h>
#include <cuda_bf16.h>
#include <cuda.h>
#include <stdint.h>

typedef __nv_bfloat16 bf16;
template <bool B> struct BoolTag { static constexpr bool value = B; };
#define UNLIKELY(x) __builtin_expect(!!(x), 0)

__device__ __forceinline__ uint32_t smem_u32(const void* p) { return (uint32_t)__cvta_generic_to_shared(p); }
__device__ __forceinline__ void mbar_init(uint32_t bar, uint32_t count) {
  asm volatile("mbarrier.init.shared::cta.b64 [%0], %1;" :: "r"(bar), "r"(count) : "memory");
}
__device__ __forceinline__ void mbar_expect_tx(uint32_t bar, uint32_t bytes) {
  asm volatile("mbarrier.arrive.expect_tx.shared::cta.b64 _, [%0], %1;" :: "r"(bar), "r"(bytes) : "memory");
}
__device__ __forceinline__ void mbar_arrive(uint32_t bar) {
  asm volatile("mbarrier.arrive.shared::cta.b64 _, [%0];" :: "r"(bar) : "memory");
}
__device__ __forceinline__ void mbar_arrive_if(uint32_t bar, bool pred) {
  asm volatile("{\n.reg .pred p;\nsetp.ne.u32 p, %1, 0;\n@p mbarrier.arrive.shared::cta.b64 _, [%0];\n}" :: "r"(bar), "r"((uint32_t)pred) : "memory");
}
__device__ __forceinline__ uint32_t mbar_arrive_if_dep(uint32_t bar, bool pred) {
  uint32_t r;
  asm volatile("{\n.reg .pred p;\n.reg .b64 st;\n.reg .b32 hi;\nmov.b64 st, 0;\nsetp.ne.u32 p, %2, 0;\n@p mbarrier.arrive.shared::cta.b64 st, [%1];\nmov.b64 {%0, hi}, st;\n}"
               : "=r"(r) : "r"(bar), "r"((uint32_t)pred) : "memory");
  return r;
}
__device__ __forceinline__ void mbar_arrive_n(uint32_t bar, uint32_t n) {
  asm volatile("mbarrier.arrive.shared::cta.b64 _, [%0], %1;" :: "r"(bar), "r"(n) : "memory");
}
__device__ __forceinline__ void mbar_arrive_cluster_n(uint32_t bar, uint32_t cta, uint32_t n) {
  asm volatile("{\n.reg .b32 ra;\nmapa.shared::cluster.u32 ra, %0, %1;\n"
               "mbarrier.arrive.shared::cluster.b64 _, [ra], %2;\n}" :: "r"(bar), "r"(cta), "r"(n) : "memory");
}
__device__ __forceinline__ void red_release_add(int* p, int v) {
  asm volatile("fence.acq_rel.gpu;\nred.relaxed.gpu.global.add.s32 [%0], %1;" :: "l"(p), "r"(v) : "memory");
}
__device__ __forceinline__ int ld_acquire(const int* p) { int v; asm volatile("ld.acquire.gpu.global.s32 %0, [%1];" : "=r"(v) : "l"(p) : "memory"); return v; }
__device__ __forceinline__ void st_shared_v4(uint32_t a, uint32_t x, uint32_t y, uint32_t z, uint32_t w) {
  asm volatile("st.shared.v4.u32 [%0], {%1, %2, %3, %4};" :: "r"(a), "r"(x), "r"(y), "r"(z), "r"(w) : "memory");
}
__device__ __forceinline__ void mbar_arrive_cluster(uint32_t bar, uint32_t cta) {
  asm volatile("{\n.reg .b32 ra;\nmapa.shared::cluster.u32 ra, %0, %1;\n"
               "mbarrier.arrive.shared::cluster.b64 _, [ra];\n}" :: "r"(bar), "r"(cta) : "memory");
}
__device__ __forceinline__ void mbar_wait(uint32_t bar, uint32_t parity) {
  asm volatile("{\n.reg .pred p;\n.reg .u32 n;\nmov.u32 n, 0;\n"
               "LAB_WAIT:\n"
               "mbarrier.try_wait.parity.shared::cta.b64 p, [%0], %1;\n"
               "@p bra LAB_DONE;\n"
               "add.u32 n, n, 1;\n"
               "setp.lt.u32 p, n, 262144;\n"
               "@p bra LAB_WAIT;\n"
               "LAB_DONE:\n}" :: "r"(bar), "r"(parity) : "memory");
}
__device__ __forceinline__ uint32_t mbar_try(uint32_t bar, uint32_t parity) {
  uint32_t ok;
  asm volatile("{\n.reg .pred p;\nmbarrier.test_wait.parity.shared::cta.b64 p, [%1], %2;\nselp.u32 %0, 1, 0, p;\n}"
               : "=r"(ok) : "r"(bar), "r"(parity) : "memory");
  return ok;
}
__device__ __forceinline__ void flag_wait_ge(const int* p, int v) {
  asm volatile("{\n.reg .pred p;\n.reg .u32 n;\n.reg .s32 x;\nmov.u32 n, 0;\n"
               "LAB_WAIT:\n"
               "ld.acquire.gpu.global.s32 x, [%0];\n"
               "setp.ge.s32 p, x, %1;\n"
               "@p bra LAB_DONE;\n"
               "nanosleep.u32 100;\n"
               "add.u32 n, n, 1;\n"
               "setp.lt.u32 p, n, 65536;\n"
               "@p bra LAB_WAIT;\n"
               "LAB_DONE:\n}" :: "l"(p), "r"(v) : "memory");
}
__device__ __forceinline__ void flag_wait_fast(const int* p, int v) {
  asm volatile("{\n.reg .pred p;\n.reg .u32 n;\n.reg .s32 x;\nmov.u32 n, 0;\n"
               "LAB_WAIT:\n"
               "ld.relaxed.gpu.global.s32 x, [%0];\n"
               "setp.ge.s32 p, x, %1;\n"
               "@p bra LAB_DONE;\n"
               "nanosleep.u32 20;\n"
               "add.u32 n, n, 1;\n"
               "setp.lt.u32 p, n, 65536;\n"
               "@p bra LAB_WAIT;\n"
               "LAB_DONE:\n}" :: "l"(p), "r"(v) : "memory");
}
__device__ __forceinline__ void flag_wait_slow(const int* p, int v) {
  asm volatile("{\n.reg .pred p;\n.reg .u32 n;\n.reg .s32 x;\nmov.u32 n, 0;\n"
               "LAB_WAIT:\n"
               "ld.acquire.gpu.global.s32 x, [%0];\n"
               "setp.ge.s32 p, x, %1;\n"
               "@p bra LAB_DONE;\n"
               "nanosleep.u32 500;\n"
               "add.u32 n, n, 1;\n"
               "setp.lt.u32 p, n, 16384;\n"
               "@p bra LAB_WAIT;\n"
               "LAB_DONE:\n}" :: "l"(p), "r"(v) : "memory");
}
__device__ __forceinline__ bool elect_one() {
  uint32_t p;
  asm volatile("{\n.reg .pred p;\nelect.sync _|p, 0xffffffff;\nselp.u32 %0, 1, 0, p;\n}" : "=r"(p));
  return p != 0;
}
__device__ __forceinline__ void fence_barrier_init() { asm volatile("fence.mbarrier_init.release.cluster;" ::: "memory"); }
__device__ __forceinline__ void fence_proxy_async_smem() { asm volatile("fence.proxy.async.shared::cta;" ::: "memory"); }
__device__ __forceinline__ void fence_proxy_async_all() { asm volatile("fence.proxy.async;" ::: "memory"); }
__device__ __forceinline__ void cluster_wait() { asm volatile("barrier.cluster.wait.acquire.aligned;" ::: "memory"); }

__device__ __forceinline__ void tma_load_2d(uint32_t dst, const CUtensorMap* m, int c0, int c1, uint32_t bar) {
  asm volatile("cp.async.bulk.tensor.2d.shared::cluster.global.mbarrier::complete_tx::bytes [%0], [%1, {%3, %4}], [%2];"
               :: "r"(dst), "l"(m), "r"(bar), "r"(c0), "r"(c1) : "memory");
}
__device__ __forceinline__ void tma_load_3d(uint32_t dst, const CUtensorMap* m, int c0, int c1, int c2, uint32_t bar) {
  asm volatile("cp.async.bulk.tensor.3d.shared::cluster.global.mbarrier::complete_tx::bytes [%0], [%1, {%3, %4, %5}], [%2];"
               :: "r"(dst), "l"(m), "r"(bar), "r"(c0), "r"(c1), "r"(c2) : "memory");
}
__device__ __forceinline__ void tma_load_3d_mc(uint32_t dst, const CUtensorMap* m, int c0, int c1, int c2, uint32_t bar, uint16_t mask) {
  asm volatile("cp.async.bulk.tensor.3d.shared::cluster.global.mbarrier::complete_tx::bytes.multicast::cluster [%0], [%1, {%3, %4, %5}], [%2], %6;"
               :: "r"(dst), "l"(m), "r"(bar), "r"(c0), "r"(c1), "r"(c2), "h"(mask) : "memory");
}
__device__ __forceinline__ void bulk_load_1d(uint32_t dst, const void* src, uint32_t bytes, uint32_t bar) {
  asm volatile("cp.async.bulk.shared::cluster.global.mbarrier::complete_tx::bytes [%0], [%1], %2, [%3];"
               :: "r"(dst), "l"(src), "r"(bytes), "r"(bar) : "memory");
}
__device__ __forceinline__ void tma_store_2d(const CUtensorMap* m, uint32_t src, int c0, int c1) {
  asm volatile("cp.async.bulk.tensor.2d.global.shared::cta.bulk_group [%0, {%2, %3}], [%1];"
               :: "l"(m), "r"(src), "r"(c0), "r"(c1) : "memory");
}
__device__ __forceinline__ void bulk_commit() { asm volatile("cp.async.bulk.commit_group;" ::: "memory"); }
template <int N> __device__ __forceinline__ void bulk_wait() { asm volatile("cp.async.bulk.wait_group %0;" :: "n"(N) : "memory"); }
__device__ __forceinline__ void prefetch_tmap(const CUtensorMap* m) { asm volatile("prefetch.tensormap [%0];" :: "l"(m) : "memory"); }

__device__ __forceinline__ void wg_fence() { asm volatile("wgmma.fence.sync.aligned;" ::: "memory"); }
__device__ __forceinline__ void wg_commit() { asm volatile("wgmma.commit_group.sync.aligned;" ::: "memory"); }
template <int N> __device__ __forceinline__ void wg_wait() { asm volatile("wgmma.wait_group.sync.aligned %0;" :: "n"(N) : "memory"); }
template <int N> __device__ __forceinline__ void reg_alloc() { asm volatile("setmaxnreg.inc.sync.aligned.u32 %0;" :: "n"(N)); }
template <int N> __device__ __forceinline__ void reg_dealloc() { asm volatile("setmaxnreg.dec.sync.aligned.u32 %0;" :: "n"(N)); }
__device__ __forceinline__ void named_bar_sync(int id, int n) { asm volatile("bar.sync %0, %1;" :: "r"(id), "r"(n) : "memory"); }
__device__ __forceinline__ void named_bar_arrive(int id, int n) { asm volatile("bar.arrive %0, %1;" :: "r"(id), "r"(n) : "memory"); }

__device__ __forceinline__ uint64_t make_desc(uint32_t addr, uint32_t lbo_bytes, uint32_t sbo_bytes, uint32_t swz) {
  return (uint64_t)((addr & 0x3FFFF) >> 4) | ((uint64_t)(lbo_bytes >> 4) << 16) | ((uint64_t)(sbo_bytes >> 4) << 32) | ((uint64_t)swz << 62);
}
__device__ __forceinline__ uint64_t desc64(uint32_t lo, uint32_t hi) { uint64_t d; asm("mov.b64 %0, {%1, %2};" : "=l"(d) : "r"(lo), "r"(hi)); return d; }
constexpr uint32_t DHI_128 = 0x40000040u;
__device__ __forceinline__ uint32_t pack_bf16(float lo, float hi) {
  uint32_t r; asm("cvt.rn.bf16x2.f32 %0, %1, %2;" : "=r"(r) : "f"(hi), "f"(lo)); return r;
}
__device__ __forceinline__ void stmatrix_x4(uint32_t addr, uint32_t r0, uint32_t r1, uint32_t r2, uint32_t r3) {
  asm volatile("stmatrix.sync.aligned.m8n8.x4.shared.b16 [%0], {%1, %2, %3, %4};" :: "r"(addr), "r"(r0), "r"(r1), "r"(r2), "r"(r3) : "memory");
}
__device__ __forceinline__ void st_global_v4(void* p, uint32_t a, uint32_t b, uint32_t c, uint32_t d) {
  asm volatile("st.global.v4.u32 [%0], {%1, %2, %3, %4};" :: "l"(p), "r"(a), "r"(b), "r"(c), "r"(d) : "memory");
}
__device__ __forceinline__ float ex2(float x) { float y; asm("ex2.approx.ftz.f32 %0, %1;" : "=f"(y) : "f"(x)); return y; }
__device__ __forceinline__ float rcp_approx(float x) { float y; asm("rcp.approx.ftz.f32 %0, %1;" : "=f"(y) : "f"(x)); return y; }
__device__ __forceinline__ int opaque_tid() { int t; asm volatile("mov.u32 %0, %%tid.x;" : "=r"(t)); return t; }
template <int NR> __device__ __forceinline__ void fence_regs(float* d) {
#pragma unroll
  for (int i = 0; i < NR; i++) asm volatile("" : "+f"(d[i]) :: "memory");
}
template <int NR> __device__ __forceinline__ void fence_regs_u(uint32_t* d) {
#pragma unroll
  for (int i = 0; i < NR; i++) asm volatile("" : "+r"(d[i]) :: "memory");
}

__device__ __forceinline__ void wgmma_rs_n128_b1(float* d, const uint32_t* a, uint64_t db, int scale_d) {
  asm volatile("{\n.reg .pred p;\nsetp.ne.b32 p, %69, 0;\n"
    "wgmma.mma_async.sync.aligned.m64n128k16.f32.bf16.bf16 {%0, %1, %2, %3, %4, %5, %6, %7, %8, %9, %10, %11, %12, %13, %14, %15, %16, %17, %18, %19, %20, %21, %22, %23, %24, %25, %26, %27, %28, %29, %30, %31, %32, %33, %34, %35, %36, %37, %38, %39, %40, %41, %42, %43, %44, %45, %46, %47, %48, %49, %50, %51, %52, %53, %54, %55, %56, %57, %58, %59, %60, %61, %62, %63}, {%64, %65, %66, %67}, %68, p, 1, 1, 1;\n}\n"
    : "+f"(d[0]), "+f"(d[1]), "+f"(d[2]), "+f"(d[3]), "+f"(d[4]), "+f"(d[5]), "+f"(d[6]), "+f"(d[7]), "+f"(d[8]), "+f"(d[9]), "+f"(d[10]), "+f"(d[11]), "+f"(d[12]), "+f"(d[13]), "+f"(d[14]), "+f"(d[15]), "+f"(d[16]), "+f"(d[17]), "+f"(d[18]), "+f"(d[19]), "+f"(d[20]), "+f"(d[21]), "+f"(d[22]), "+f"(d[23]), "+f"(d[24]), "+f"(d[25]), "+f"(d[26]), "+f"(d[27]), "+f"(d[28]), "+f"(d[29]), "+f"(d[30]), "+f"(d[31]), "+f"(d[32]), "+f"(d[33]), "+f"(d[34]), "+f"(d[35]), "+f"(d[36]), "+f"(d[37]), "+f"(d[38]), "+f"(d[39]), "+f"(d[40]), "+f"(d[41]), "+f"(d[42]), "+f"(d[43]), "+f"(d[44]), "+f"(d[45]), "+f"(d[46]), "+f"(d[47]), "+f"(d[48]), "+f"(d[49]), "+f"(d[50]), "+f"(d[51]), "+f"(d[52]), "+f"(d[53]), "+f"(d[54]), "+f"(d[55]), "+f"(d[56]), "+f"(d[57]), "+f"(d[58]), "+f"(d[59]), "+f"(d[60]), "+f"(d[61]), "+f"(d[62]), "+f"(d[63])
    : "r"(a[0]), "r"(a[1]), "r"(a[2]), "r"(a[3]), "l"(db), "r"(scale_d));
}
__device__ __forceinline__ void wgmma_rs_n32_b1(float* d, const uint32_t* a, uint64_t db, int scale_d) {
  asm volatile("{\n.reg .pred p;\nsetp.ne.b32 p, %21, 0;\n"
    "wgmma.mma_async.sync.aligned.m64n32k16.f32.bf16.bf16 {%0, %1, %2, %3, %4, %5, %6, %7, %8, %9, %10, %11, %12, %13, %14, %15}, {%16, %17, %18, %19}, %20, p, 1, 1, 1;\n}\n"
    : "+f"(d[0]), "+f"(d[1]), "+f"(d[2]), "+f"(d[3]), "+f"(d[4]), "+f"(d[5]), "+f"(d[6]), "+f"(d[7]), "+f"(d[8]), "+f"(d[9]), "+f"(d[10]), "+f"(d[11]), "+f"(d[12]), "+f"(d[13]), "+f"(d[14]), "+f"(d[15])
    : "r"(a[0]), "r"(a[1]), "r"(a[2]), "r"(a[3]), "l"(db), "r"(scale_d));
}
__device__ __forceinline__ void wgmma_rs_n40_b1(float* d, const uint32_t* a, uint64_t db, int scale_d) {
  asm volatile("{\n.reg .pred p;\nsetp.ne.b32 p, %25, 0;\n"
    "wgmma.mma_async.sync.aligned.m64n40k16.f32.bf16.bf16 {%0, %1, %2, %3, %4, %5, %6, %7, %8, %9, %10, %11, %12, %13, %14, %15, %16, %17, %18, %19}, {%20, %21, %22, %23}, %24, p, 1, 1, 1;\n}\n"
    : "+f"(d[0]), "+f"(d[1]), "+f"(d[2]), "+f"(d[3]), "+f"(d[4]), "+f"(d[5]), "+f"(d[6]), "+f"(d[7]), "+f"(d[8]), "+f"(d[9]), "+f"(d[10]), "+f"(d[11]), "+f"(d[12]), "+f"(d[13]), "+f"(d[14]), "+f"(d[15]), "+f"(d[16]), "+f"(d[17]), "+f"(d[18]), "+f"(d[19])
    : "r"(a[0]), "r"(a[1]), "r"(a[2]), "r"(a[3]), "l"(db), "r"(scale_d));
}
__device__ __forceinline__ void wgmma_ss_n128_a0b0(float* d, uint64_t da, uint64_t db, int scale_d) {
  asm volatile("{\n.reg .pred p;\nsetp.ne.b32 p, %66, 0;\n"
    "wgmma.mma_async.sync.aligned.m64n128k16.f32.bf16.bf16 {%0, %1, %2, %3, %4, %5, %6, %7, %8, %9, %10, %11, %12, %13, %14, %15, %16, %17, %18, %19, %20, %21, %22, %23, %24, %25, %26, %27, %28, %29, %30, %31, %32, %33, %34, %35, %36, %37, %38, %39, %40, %41, %42, %43, %44, %45, %46, %47, %48, %49, %50, %51, %52, %53, %54, %55, %56, %57, %58, %59, %60, %61, %62, %63}, %64, %65, p, 1, 1, 0, 0;\n}\n"
    : "+f"(d[0]), "+f"(d[1]), "+f"(d[2]), "+f"(d[3]), "+f"(d[4]), "+f"(d[5]), "+f"(d[6]), "+f"(d[7]), "+f"(d[8]), "+f"(d[9]), "+f"(d[10]), "+f"(d[11]), "+f"(d[12]), "+f"(d[13]), "+f"(d[14]), "+f"(d[15]), "+f"(d[16]), "+f"(d[17]), "+f"(d[18]), "+f"(d[19]), "+f"(d[20]), "+f"(d[21]), "+f"(d[22]), "+f"(d[23]), "+f"(d[24]), "+f"(d[25]), "+f"(d[26]), "+f"(d[27]), "+f"(d[28]), "+f"(d[29]), "+f"(d[30]), "+f"(d[31]), "+f"(d[32]), "+f"(d[33]), "+f"(d[34]), "+f"(d[35]), "+f"(d[36]), "+f"(d[37]), "+f"(d[38]), "+f"(d[39]), "+f"(d[40]), "+f"(d[41]), "+f"(d[42]), "+f"(d[43]), "+f"(d[44]), "+f"(d[45]), "+f"(d[46]), "+f"(d[47]), "+f"(d[48]), "+f"(d[49]), "+f"(d[50]), "+f"(d[51]), "+f"(d[52]), "+f"(d[53]), "+f"(d[54]), "+f"(d[55]), "+f"(d[56]), "+f"(d[57]), "+f"(d[58]), "+f"(d[59]), "+f"(d[60]), "+f"(d[61]), "+f"(d[62]), "+f"(d[63])
    : "l"(da), "l"(db), "r"(scale_d));
}
__device__ __forceinline__ void wgmma_ss_n128_a0b1(float* d, uint64_t da, uint64_t db, int scale_d) {
  asm volatile("{\n.reg .pred p;\nsetp.ne.b32 p, %66, 0;\n"
    "wgmma.mma_async.sync.aligned.m64n128k16.f32.bf16.bf16 {%0, %1, %2, %3, %4, %5, %6, %7, %8, %9, %10, %11, %12, %13, %14, %15, %16, %17, %18, %19, %20, %21, %22, %23, %24, %25, %26, %27, %28, %29, %30, %31, %32, %33, %34, %35, %36, %37, %38, %39, %40, %41, %42, %43, %44, %45, %46, %47, %48, %49, %50, %51, %52, %53, %54, %55, %56, %57, %58, %59, %60, %61, %62, %63}, %64, %65, p, 1, 1, 0, 1;\n}\n"
    : "+f"(d[0]), "+f"(d[1]), "+f"(d[2]), "+f"(d[3]), "+f"(d[4]), "+f"(d[5]), "+f"(d[6]), "+f"(d[7]), "+f"(d[8]), "+f"(d[9]), "+f"(d[10]), "+f"(d[11]), "+f"(d[12]), "+f"(d[13]), "+f"(d[14]), "+f"(d[15]), "+f"(d[16]), "+f"(d[17]), "+f"(d[18]), "+f"(d[19]), "+f"(d[20]), "+f"(d[21]), "+f"(d[22]), "+f"(d[23]), "+f"(d[24]), "+f"(d[25]), "+f"(d[26]), "+f"(d[27]), "+f"(d[28]), "+f"(d[29]), "+f"(d[30]), "+f"(d[31]), "+f"(d[32]), "+f"(d[33]), "+f"(d[34]), "+f"(d[35]), "+f"(d[36]), "+f"(d[37]), "+f"(d[38]), "+f"(d[39]), "+f"(d[40]), "+f"(d[41]), "+f"(d[42]), "+f"(d[43]), "+f"(d[44]), "+f"(d[45]), "+f"(d[46]), "+f"(d[47]), "+f"(d[48]), "+f"(d[49]), "+f"(d[50]), "+f"(d[51]), "+f"(d[52]), "+f"(d[53]), "+f"(d[54]), "+f"(d[55]), "+f"(d[56]), "+f"(d[57]), "+f"(d[58]), "+f"(d[59]), "+f"(d[60]), "+f"(d[61]), "+f"(d[62]), "+f"(d[63])
    : "l"(da), "l"(db), "r"(scale_d));
}
__device__ __forceinline__ void wgmma_ss_n256_a0b1(float* d, uint64_t da, uint64_t db, int scale_d) {
  asm volatile("{\n.reg .pred p;\nsetp.ne.b32 p, %130, 0;\n"
    "wgmma.mma_async.sync.aligned.m64n256k16.f32.bf16.bf16 {%0, %1, %2, %3, %4, %5, %6, %7, %8, %9, %10, %11, %12, %13, %14, %15, %16, %17, %18, %19, %20, %21, %22, %23, %24, %25, %26, %27, %28, %29, %30, %31, %32, %33, %34, %35, %36, %37, %38, %39, %40, %41, %42, %43, %44, %45, %46, %47, %48, %49, %50, %51, %52, %53, %54, %55, %56, %57, %58, %59, %60, %61, %62, %63, %64, %65, %66, %67, %68, %69, %70, %71, %72, %73, %74, %75, %76, %77, %78, %79, %80, %81, %82, %83, %84, %85, %86, %87, %88, %89, %90, %91, %92, %93, %94, %95, %96, %97, %98, %99, %100, %101, %102, %103, %104, %105, %106, %107, %108, %109, %110, %111, %112, %113, %114, %115, %116, %117, %118, %119, %120, %121, %122, %123, %124, %125, %126, %127}, %128, %129, p, 1, 1, 0, 1;\n}\n"
    : "+f"(d[0]), "+f"(d[1]), "+f"(d[2]), "+f"(d[3]), "+f"(d[4]), "+f"(d[5]), "+f"(d[6]), "+f"(d[7]), "+f"(d[8]), "+f"(d[9]), "+f"(d[10]), "+f"(d[11]), "+f"(d[12]), "+f"(d[13]), "+f"(d[14]), "+f"(d[15]), "+f"(d[16]), "+f"(d[17]), "+f"(d[18]), "+f"(d[19]), "+f"(d[20]), "+f"(d[21]), "+f"(d[22]), "+f"(d[23]), "+f"(d[24]), "+f"(d[25]), "+f"(d[26]), "+f"(d[27]), "+f"(d[28]), "+f"(d[29]), "+f"(d[30]), "+f"(d[31]), "+f"(d[32]), "+f"(d[33]), "+f"(d[34]), "+f"(d[35]), "+f"(d[36]), "+f"(d[37]), "+f"(d[38]), "+f"(d[39]), "+f"(d[40]), "+f"(d[41]), "+f"(d[42]), "+f"(d[43]), "+f"(d[44]), "+f"(d[45]), "+f"(d[46]), "+f"(d[47]), "+f"(d[48]), "+f"(d[49]), "+f"(d[50]), "+f"(d[51]), "+f"(d[52]), "+f"(d[53]), "+f"(d[54]), "+f"(d[55]), "+f"(d[56]), "+f"(d[57]), "+f"(d[58]), "+f"(d[59]), "+f"(d[60]), "+f"(d[61]), "+f"(d[62]), "+f"(d[63]), "+f"(d[64]), "+f"(d[65]), "+f"(d[66]), "+f"(d[67]), "+f"(d[68]), "+f"(d[69]), "+f"(d[70]), "+f"(d[71]), "+f"(d[72]), "+f"(d[73]), "+f"(d[74]), "+f"(d[75]), "+f"(d[76]), "+f"(d[77]), "+f"(d[78]), "+f"(d[79]), "+f"(d[80]), "+f"(d[81]), "+f"(d[82]), "+f"(d[83]), "+f"(d[84]), "+f"(d[85]), "+f"(d[86]), "+f"(d[87]), "+f"(d[88]), "+f"(d[89]), "+f"(d[90]), "+f"(d[91]), "+f"(d[92]), "+f"(d[93]), "+f"(d[94]), "+f"(d[95]), "+f"(d[96]), "+f"(d[97]), "+f"(d[98]), "+f"(d[99]), "+f"(d[100]), "+f"(d[101]), "+f"(d[102]), "+f"(d[103]), "+f"(d[104]), "+f"(d[105]), "+f"(d[106]), "+f"(d[107]), "+f"(d[108]), "+f"(d[109]), "+f"(d[110]), "+f"(d[111]), "+f"(d[112]), "+f"(d[113]), "+f"(d[114]), "+f"(d[115]), "+f"(d[116]), "+f"(d[117]), "+f"(d[118]), "+f"(d[119]), "+f"(d[120]), "+f"(d[121]), "+f"(d[122]), "+f"(d[123]), "+f"(d[124]), "+f"(d[125]), "+f"(d[126]), "+f"(d[127])
    : "l"(da), "l"(db), "r"(scale_d));
}
__device__ __forceinline__ void wgmma_ss_n40_a1b1(float* d, uint64_t da, uint64_t db, int scale_d) {
  asm volatile("{\n.reg .pred p;\nsetp.ne.b32 p, %22, 0;\n"
    "wgmma.mma_async.sync.aligned.m64n40k16.f32.bf16.bf16 {%0, %1, %2, %3, %4, %5, %6, %7, %8, %9, %10, %11, %12, %13, %14, %15, %16, %17, %18, %19}, %20, %21, p, 1, 1, 1, 1;\n}\n"
    : "+f"(d[0]), "+f"(d[1]), "+f"(d[2]), "+f"(d[3]), "+f"(d[4]), "+f"(d[5]), "+f"(d[6]), "+f"(d[7]), "+f"(d[8]), "+f"(d[9]), "+f"(d[10]), "+f"(d[11]), "+f"(d[12]), "+f"(d[13]), "+f"(d[14]), "+f"(d[15]), "+f"(d[16]), "+f"(d[17]), "+f"(d[18]), "+f"(d[19])
    : "l"(da), "l"(db), "r"(scale_d));
}


constexpr int S_LEN = 2048;
constexpr int PANEL_ELEMS = S_LEN * 64;
constexpr float LOG2E = 1.4426950408889634f;
constexpr float SM_SCALE = 0.08838834764831845f * LOG2E;

__device__ __align__(1024) bf16 g_qkv[224 * PANEL_ELEMS];
__device__ __align__(1024) bf16 g_a3[80 * PANEL_ELEMS];
__device__ float g_gate[S_LEN];
__device__ __align__(1024) uint4 g_kvimg[32 * 5 * 64];
constexpr int F_PROJ = 0;
constexpr int F_READY = 16;
constexpr int F_START3 = 24;
constexpr int F_NEXT = 20;
constexpr int F_OWN = 48;
constexpr int F_KV = 32;
constexpr int F_O = 64;
constexpr int F_CTX = 128;
constexpr int F_TOTAL = 192;
__device__ int g_flags[2][F_TOTAL];
__device__ int g_epoch;


__device__ __forceinline__ void hedgehog_phi(const float* p, uint32_t* phi  ) {
  float mx0 = p[0], mn0 = p[0], mx1 = p[2], mn1 = p[2];
#pragma unroll
  for (int j = 0; j < 4; j++) {
    mx0 = fmaxf(mx0, fmaxf(p[4 * j], p[4 * j + 1])); mn0 = fminf(mn0, fminf(p[4 * j], p[4 * j + 1]));
    mx1 = fmaxf(mx1, fmaxf(p[4 * j + 2], p[4 * j + 3])); mn1 = fminf(mn1, fminf(p[4 * j + 2], p[4 * j + 3]));
  }
#pragma unroll
  for (int o = 1; o <= 2; o <<= 1) {
    mx0 = fmaxf(mx0, __shfl_xor_sync(0xffffffffu, mx0, o)); mn0 = fminf(mn0, __shfl_xor_sync(0xffffffffu, mn0, o));
    mx1 = fmaxf(mx1, __shfl_xor_sync(0xffffffffu, mx1, o)); mn1 = fminf(mn1, __shfl_xor_sync(0xffffffffu, mn1, o));
  }
  mx0 *= LOG2E; mn0 *= LOG2E; mx1 *= LOG2E; mn1 *= LOG2E;
  float ep[16], en[16];
  float sp0 = 0.f, sn0 = 0.f, sp1 = 0.f, sn1 = 0.f;
#pragma unroll
  for (int j = 0; j < 4; j++) {
#pragma unroll
    for (int e = 0; e < 2; e++) {
      ep[4 * j + e] = ex2(fmaf(p[4 * j + e], LOG2E, -mx0)); sp0 += ep[4 * j + e];
      en[4 * j + e] = ex2(fmaf(p[4 * j + e], -LOG2E, mn0)); sn0 += en[4 * j + e];
      ep[4 * j + 2 + e] = ex2(fmaf(p[4 * j + 2 + e], LOG2E, -mx1)); sp1 += ep[4 * j + 2 + e];
      en[4 * j + 2 + e] = ex2(fmaf(p[4 * j + 2 + e], -LOG2E, mn1)); sn1 += en[4 * j + 2 + e];
    }
  }
#pragma unroll
  for (int o = 1; o <= 2; o <<= 1) {
    sp0 += __shfl_xor_sync(0xffffffffu, sp0, o); sn0 += __shfl_xor_sync(0xffffffffu, sn0, o);
    sp1 += __shfl_xor_sync(0xffffffffu, sp1, o); sn1 += __shfl_xor_sync(0xffffffffu, sn1, o);
  }
  sp0 = rcp_approx(sp0); sn0 = rcp_approx(sn0); sp1 = rcp_approx(sp1); sn1 = rcp_approx(sn1);
#pragma unroll
  for (int j = 0; j < 4; j++) {
    phi[2 * j] = pack_bf16(ep[4 * j] * sp0, ep[4 * j + 1] * sp0);
    phi[2 * j + 1] = pack_bf16(ep[4 * j + 2] * sp1, ep[4 * j + 3] * sp1);
    phi[8 + 2 * j] = pack_bf16(en[4 * j] * sn0, en[4 * j + 1] * sn0);
    phi[8 + 2 * j + 1] = pack_bf16(en[4 * j + 2] * sn1, en[4 * j + 3] * sn1);
  }
}

__device__ __forceinline__ void hedgehog_exp(const float* p, uint32_t* e  ) {
  float mx0 = p[0], mn0 = p[0], mx1 = p[2], mn1 = p[2];
#pragma unroll
  for (int j = 0; j < 4; j++) {
    mx0 = fmaxf(mx0, fmaxf(p[4 * j], p[4 * j + 1])); mn0 = fminf(mn0, fminf(p[4 * j], p[4 * j + 1]));
    mx1 = fmaxf(mx1, fmaxf(p[4 * j + 2], p[4 * j + 3])); mn1 = fminf(mn1, fminf(p[4 * j + 2], p[4 * j + 3]));
  }
#pragma unroll
  for (int o = 1; o <= 2; o <<= 1) {
    mx0 = fmaxf(mx0, __shfl_xor_sync(0xffffffffu, mx0, o)); mn0 = fminf(mn0, __shfl_xor_sync(0xffffffffu, mn0, o));
    mx1 = fmaxf(mx1, __shfl_xor_sync(0xffffffffu, mx1, o)); mn1 = fminf(mn1, __shfl_xor_sync(0xffffffffu, mn1, o));
  }
  mx0 *= LOG2E; mn0 *= LOG2E; mx1 *= LOG2E; mn1 *= LOG2E;
#pragma unroll
  for (int j = 0; j < 4; j++) {
    e[2 * j] = pack_bf16(ex2(fmaf(p[4 * j], LOG2E, -mx0)), ex2(fmaf(p[4 * j + 1], LOG2E, -mx0)));
    e[2 * j + 1] = pack_bf16(ex2(fmaf(p[4 * j + 2], LOG2E, -mx1)), ex2(fmaf(p[4 * j + 3], LOG2E, -mx1)));
    e[8 + 2 * j] = pack_bf16(ex2(fmaf(p[4 * j], -LOG2E, mn0)), ex2(fmaf(p[4 * j + 1], -LOG2E, mn0)));
    e[8 + 2 * j + 1] = pack_bf16(ex2(fmaf(p[4 * j + 2], -LOG2E, mn1)), ex2(fmaf(p[4 * j + 3], -LOG2E, mn1)));
  }
}

constexpr int MAXT1 = 12;
struct Params {
  CUtensorMap mX, mC, mW[4]  , mWphi, mQKV, mA3, mWo, mWo2, mOut;
  const bf16 *x, *gate_w;
  uint32_t zero;
  int korder[5];
  uint16_t l1[132][MAXT1];
  uint16_t t3[132];
  uint16_t items[520];
};
enum { T_BQ = 0, T_BK = 1, T_BV = 2, T_AQ = 3, T_AKV = 4 };
constexpr int ST1 = 4, STB1 = 49152;
constexpr int ST3 = 6;
constexpr int VST = 3;
constexpr int SMEM_BYTES = 7 * 32768 + 1024 + 640;
constexpr int OWN_CUT = 8, NOWN = 4 * (16 - OWN_CUT) - 1;
constexpr int QAHEAD = 2;

__global__ void __cluster_dims__(2, 1, 1) __launch_bounds__(384, 1) fused_kernel(const __grid_constant__ Params P) {
  extern __shared__ uint8_t smem_raw[];
  const uint32_t sbase = (smem_u32(smem_raw) + 1023) & ~1023u;
  const uint32_t sdesc = __shfl_sync(0xffffffffu, (sbase & 0x3FFFF) >> 4, 0);
  const uint32_t bars = sbase + 7 * 32768;
  const uint32_t full1 = bars, empty1 = bars + 32;
  const uint32_t qfull = bars + 64, qempty = bars + 80, kfull = bars + 96, kempty = bars + 112, vfull = bars + 128, vempty = bars + 160;
  const uint32_t full3 = bars + 192, empty3 = bars + 240, sig = bars + 480, dep3 = bars + 296, qgo = bars + 336, go3 = bars + 344, scode = bars + 352, cfull = bars + 384, lastdst = bars + 448;
  const uint32_t sK = sbase, sV = sbase + 2 * 32768, sQ0 = sbase + 6 * 32768;
  const int tid = threadIdx.x;
  const int warp = __shfl_sync(0xffffffffu, tid >> 5, 0), lane = tid & 31, wg = warp >> 2;
  const int cta = blockIdx.x;
  const int s0 = P.l1[cta][MAXT1 - 1];
  const uint16_t* l1 = P.l1[cta];
  const uint32_t rank = cta & 1;
  auto p1_load = [&](int code, int ks, int s, bool mc) {
    const int type = code >> 9, n = (code >> 4) & 31, m = code & 15;
    const CUtensorMap* mA = (type == T_BK || type == T_BV) ? &P.mC : &P.mX;
    const CUtensorMap* mB = &P.mW[type < 3 ? type : 3];
    const uint32_t full = full1 + 8 * s, a = sbase + s * STB1;
    mbar_expect_tx(full, STB1);
    tma_load_2d(a, mA, ks * 64, m * 128, full);
    const int p0 = type == T_AKV ? 16 + 2 * n : 4 * n, p1 = type == T_AKV ? 32 + 2 * n : 4 * n + 2;
    if (mc) {
      tma_load_3d_mc(a + 16384 + rank * 16384, mB, 0, ks * 64, rank ? p1 : p0, full, 3);
    } else {
      tma_load_3d(a + 16384, mB, 0, ks * 64, p0, full);
      tma_load_3d(a + 32768, mB, 0, ks * 64, p1, full);
    }
  };
  if (warp == 10) {
    if (lane < 12) prefetch_tmap(&P.mX + lane);
  }
  if (warp == 8) {
    if (elect_one()) {
      for (int s = 0; s < ST1; s++) { mbar_init(full1 + 8 * s, 1); mbar_init(empty1 + 8 * s, 16); }
      for (int s = 0; s < s0; s++) { mbar_arrive(full1 + 8 * s); mbar_arrive_n(empty1 + 8 * s, 16); }
      fence_barrier_init();
      fence_proxy_async_smem();
      for (int ks = 0; ks < ST1; ks++) p1_load(l1[0], ks, (s0 + ks) & 3, false);
    }
  } else if (warp == 9) {
    if (elect_one()) {
      for (int s = 0; s < 2; s++) { mbar_init(qfull + 8 * s, 1); mbar_init(qempty + 8 * s, 8); mbar_init(kfull + 8 * s, 1); mbar_init(kempty + 8 * s, 8); }
      for (int s = 0; s < VST; s++) { mbar_init(vfull + 8 * s, 1); mbar_init(vempty + 8 * s, 8); }
      for (int s = 0; s < ST3; s++) { mbar_init(full3 + 8 * s, 1); mbar_init(empty3 + 8 * s, 16); }
      mbar_init(qgo, 1); mbar_init(go3, 1);
      for (int s = 0; s < 8; s++) { mbar_init(sig + 8 * s, 8); mbar_init(cfull + 8 * s, 1); }
      for (int s = 0; s < 5; s++) mbar_init(dep3 + 8 * s, 1);
      fence_barrier_init();
    }
  }
  __syncthreads();
  asm volatile("barrier.cluster.arrive.relaxed.aligned;" ::: "memory");
  cluster_wait();
  auto item_code = [&](int it) { int v; asm volatile("ld.shared.u32 %0, [%1];" : "=r"(v) : "r"(scode + 4 * (it & 7)) : "memory"); return __shfl_sync(0xffffffffu, v, 0); };

  if (wg == 2) {
    reg_dealloc<24>();
    const int which = warp - 8;
    int s = 0, ph = 0;
    int epoch = 0;
    if (which != 0) epoch = __ldcg(&g_epoch);
    int* flags = g_flags[epoch & 1];
    if (which == 3) {
      if (cta == 0) for (int i = lane; i < F_TOTAL; i += 32) g_flags[(epoch & 1) ^ 1][i] = 0;
#pragma unroll 1
      for (int it = 0; it < MAXT1; it++) {
        const int code = l1[it];
        if (code == 0xFFFF) break;
        const int type = code >> 9, n = (code >> 4) & 31;
        mbar_wait(sig + 8 * (ph & 7), (ph >> 3) & 1); ph++;
        if (l1[it + 1] == 0xFFFF && elect_one()) {
          for (int w = 0; w < 2; w++) {
            uint64_t d;
            asm volatile("ld.shared.u64 %0, [%1];" : "=l"(d) : "r"(lastdst + 8 * w) : "memory");
            for (int p = 0; p < 4; p++)
              asm volatile("cp.async.bulk.global.shared::cta.bulk_group [%0], [%1], 8192;" :: "l"(d + (uint64_t)p * PANEL_ELEMS * 2), "r"(sbase + (3 + w) * 32768 + p * 8192) : "memory");
          }
          bulk_commit();
          asm volatile("cp.async.bulk.wait_group.read 0;" ::: "memory");
          mbar_arrive_n(vempty + 8, 8); mbar_arrive_n(vempty + 16, 8);
          bulk_wait<0>();
          fence_proxy_async_all();
        }
        __syncwarp();
        if (elect_one()) red_release_add(flags + (type == T_AKV ? F_KV + n : type == T_AQ ? F_O + (code & 15) : F_PROJ + n), 1);
      }
#pragma unroll 1
      for (int it = 0;; it++) {
        mbar_wait(cfull + 8 * (it & 7), (it >> 3) & 1);
        const int code = item_code(it);
        if (code == 0xFFFF) break;
        mbar_wait(sig + 8 * (ph & 7), (ph >> 3) & 1); ph++;
        if (elect_one()) red_release_add(flags + F_CTX + (code & 15) * 4 + (code >> 7), 1);
      }
    } else {
      int verified = 0;
      int own = P.t3[cta] == 0xFFFF ? 8 : (P.t3[cta] & 15) >> 1;
      auto pop_item = [&](int it) {
        int idx = 0;
        if (own < 8) {
          if (lane == 0) idx = atomicAdd(flags + F_OWN + own, 1);
          idx = __shfl_sync(0xffffffffu, idx, 0);
          if (idx < NOWN) idx += own * NOWN; else own = 8;
        }
        if (own == 8) {
          if (lane == 0) idx = atomicAdd(flags + F_NEXT, 1);
          idx = __shfl_sync(0xffffffffu, idx, 0) + 8 * NOWN;
        }
        const int code = P.items[idx < 512 ? idx : 512];
        if (code != 0xFFFF && !((verified >> (code >> 5)) & 1)) {
          flag_wait_ge(flags + F_PROJ + (code >> 5), 48);
          verified = __ballot_sync(0xffffffffu, ld_acquire(flags + F_PROJ + (lane & 15)) >= 48);
          if (it == 0) flag_wait_ge(flags + F_READY, 128);
          fence_proxy_async_all();
        }
        if (elect_one()) {
          asm volatile("st.shared.u32 [%0], %1;" :: "r"(scode + 4 * (it & 7)), "r"(code) : "memory");
          mbar_arrive(cfull + 8 * (it & 7));
        }
      };
      int p1par = 0;
      if (which == 0) {
        s = s0; ph = 0;
#pragma unroll 1
        for (int it = 0; it < MAXT1; it++) {
          const int code = l1[it];
          if (code == 0xFFFF) break;
          const int type = code >> 9, n = (code >> 4) & 31;
          const int KS = (type == T_BK || type == T_BV) ? 8 : 16;
          const int qarm = l1[it + 1] == 0xFFFF ? KS - 3 : -1;
#pragma unroll 1
          for (int ks = it == 0 ? ST1 : 0; ks < KS; ks++) {
            mbar_wait(empty1 + 8 * s, ph);
            if (elect_one()) {
              p1_load(code, ks, s, true);
              if (ks == qarm) { mbar_arrive_n(qempty, 8); mbar_arrive(qgo); }
            }
            if (++s == ST1) { s = 0; ph ^= 1; }
          }
          if (it == 0) flags = g_flags[__ldcg(&g_epoch) & 1];
          if (type >= T_AQ) {
            mbar_wait(empty1 + 8 * s, ph);
            if (elect_one()) {
              const uint32_t full = full1 + 8 * s, a = sbase + s * STB1;
              mbar_expect_tx(full, type == T_AKV ? 8192 : 16384);
              tma_load_2d(a, &P.mWphi, 0, type == T_AKV ? n * 128 : n * 256, full);
              if (type == T_AQ) tma_load_2d(a + 8192, &P.mWphi, 0, n * 256 + 128, full);
            }
            if (++s == ST1) { s = 0; ph ^= 1; }
            if (type == T_AQ) {
              flag_wait_ge(flags + F_READY, 128);
              fence_proxy_async_all();
              mbar_wait(empty1 + 8 * s, ph);
              if (elect_one()) {
                mbar_expect_tx(full1 + 8 * s, 40960);
                bulk_load_1d(sbase + s * STB1, g_kvimg + n * 8 * 320, 40960, full1 + 8 * s);
              }
              if (++s == ST1) { s = 0; ph ^= 1; }
            }
          }
        }
        p1par = ph;
        mbar_wait(empty1, p1par);
        if (elect_one()) mbar_arrive_n(kempty, 8);
      } else if (cta < 128) {
#pragma unroll 1
        for (int r = which - 1; r < 16; r += 2) {
          const int row = cta * 16 + r;
          const uint4* xr = reinterpret_cast<const uint4*>(P.x + (size_t)row * 1024) + lane;
          const uint4* gw = reinterpret_cast<const uint4*>(P.gate_w) + lane;
          float acc = 0.f;
#pragma unroll 1
          for (int i = 0; i < 4; i++) {
            const uint4 a = xr[32 * i], b = gw[32 * i];
            const uint32_t av[4] = {a.x, a.y, a.z, a.w}, bv[4] = {b.x, b.y, b.z, b.w};
#pragma unroll
            for (int j = 0; j < 4; j++) {
              acc = fmaf(__uint_as_float(av[j] << 16), __uint_as_float(bv[j] << 16), acc);
              acc = fmaf(__uint_as_float(av[j] & 0xffff0000u), __uint_as_float(bv[j] & 0xffff0000u), acc);
            }
          }
#pragma unroll
          for (int o = 16; o > 0; o >>= 1) acc += __shfl_xor_sync(0xffffffffu, acc, o);
          if (lane == 0) g_gate[row] = 1.0f / (1.0f + __expf(-acc));
        }
        const int h = cta >> 2, w4 = cta & 3;
        { int ia = 0; while (l1[ia] != 0xFFFF && (l1[ia] >> 9) != T_AKV) ia++; if (l1[ia] != 0xFFFF) mbar_wait(sig + 8 * ia, 0); }
        flag_wait_slow(flags + F_KV + (h >> 2), 16);
        const uint32_t tmp = sQ0 + (which - 1) * 16384 + lane * 16;
#pragma unroll 1
        for (int j = which - 1; j < 5; j += 2) {
          const float4* src = reinterpret_cast<const float4*>(g_qkv + (size_t)(192 + (h & ~3) + (j >> 1)) * PANEL_ELEMS +
                                                              ((h & 1) * 64 + w4 * 16 + (lane >> 2) + (j & 1) * 8) * 64 + ((h >> 1) & 1) * 32 + (lane & 3) * 8);
#pragma unroll
          for (int mm = 0; mm < 16; mm++)
            asm volatile("cp.async.cg.shared.global [%0], [%1], 16;" :: "r"(tmp + mm * 512), "l"(src + mm * (128 * 64 / 8)) : "memory");
          asm volatile("cp.async.wait_all;" ::: "memory");
          float4 a = make_float4(0.f, 0.f, 0.f, 0.f);
#pragma unroll 2
          for (int mm = 0; mm < 16; mm++) {
            float4 v;
            asm volatile("ld.shared.v4.f32 {%0, %1, %2, %3}, [%4];" : "=f"(v.x), "=f"(v.y), "=f"(v.z), "=f"(v.w) : "r"(tmp + mm * 512) : "memory");
            a.x += v.x; a.y += v.y; a.z += v.z; a.w += v.w;
          }
          const int f = w4 * 16 + (lane >> 2), q = lane & 3;
          uint32_t* dst = reinterpret_cast<uint32_t*>(g_kvimg + (h * 5 + (j < 4 ? q : 4)) * 64 + f) + (j < 4 ? j : q);
          dst[0] = pack_bf16(a.x, j < 4 ? a.y : 1.0f);
          dst[8 * 4] = pack_bf16(a.z, j < 4 ? a.w : 1.0f);
        }
        fence_proxy_async_all();
        named_bar_sync(4, 64);
        if (which == 1 && elect_one()) red_release_add(flags + F_READY, 1);
      }
      const int nst = which == 1 ? VST : 2;
      const uint32_t buf = which == 0 ? sK : which == 1 ? sV : sQ0;
      const uint32_t fullb = which == 0 ? kfull : which == 1 ? vfull : qfull;
      const uint32_t emptyb = which == 0 ? kempty : which == 1 ? vempty : qempty;
      s = 0; ph = 0;
      {
        auto hand_over_rest = [&]() {
          mbar_wait(empty1 + 8, p1par);
          if (elect_one()) { mbar_arrive_n(kempty + 8, 8); mbar_arrive_n(vempty, 8); }
          mbar_wait(empty1 + 24, p1par);
          if (elect_one()) mbar_arrive_n(qempty + 8, 8);
        };
        const int pbase = which == 0 ? 64 : which == 1 ? 128 : 0;
        const int bstride = which == 2 ? -32768 : 32768;
#pragma unroll 1
        for (int it = 0;; it++) {
          if (which == 2) { mbar_wait(qgo, it & 1); pop_item(it); }
          mbar_wait(cfull + 8 * (it & 7), (it >> 3) & 1);
          const int code = item_code(it);
          if (code == 0xFFFF) {
            if (which == 2) {
              mbar_wait(emptyb + 8 * s, ph);
              if (elect_one()) mbar_arrive(fullb + 8 * s);
            }
            if (which == 0 && it == 0) hand_over_rest();
            break;
          }
          const int h = code >> 4, qt = code & 15;
          const int jpop = which == 0 ? (qt < QAHEAD ? qt : QAHEAD) : -1;
          const int jend = which == 2 ? qt : 0;
#pragma unroll 1
          for (int j = qt; j >= jend; j--) {
            mbar_wait(emptyb + 8 * s, ph);
            if (elect_one()) {
              mbar_expect_tx(fullb + 8 * s, 32768);
              tma_load_3d(buf + s * bstride, &P.mQKV, 0, j * 128, pbase + 2 * h, fullb + 8 * s);
              if (j == jpop) mbar_arrive(qgo);
            }
            if (which == 0 && it == 0 && j == qt) hand_over_rest();
            if (++s == nst) { s = 0; ph ^= 1; }
          }
        }
      }
      const int t3 = P.t3[cta], m3 = t3 & 15, n3 = t3 >> 4;
      if (t3 != 0xFFFF) {
        if (which == 2) {
          flag_wait_ge(flags + F_O + m3, 4);
          fence_proxy_async_all();
          if (elect_one()) mbar_arrive(dep3);
        }
#pragma unroll 1
        for (int i = 0; i < nst; i++) {
          mbar_wait(emptyb + 8 * s, ph);
          const int b = which == 0 ? s : which == 1 ? 2 + s : 6 - s;
          if (b < ST3 && elect_one()) { mbar_arrive_cluster_n(empty3 + 8 * b, 0, 8); mbar_arrive_cluster_n(empty3 + 8 * b, 1, 8); }
          if (++s == nst) { s = 0; ph ^= 1; }
        }
        if (which == 0 && elect_one()) atomicAdd(flags + F_START3, 1);
        if (which == 2) {
          flag_wait_fast(flags + F_START3, 128);
          if (elect_one()) mbar_arrive(go3);
#pragma unroll 1
          for (int kg = 1; kg < 5; kg++) {
            const int grp = P.korder[kg];
            flag_wait_ge(flags + F_CTX + m3 * 4 + grp, 8);
            fence_proxy_async_all();
            if (elect_one()) mbar_arrive(dep3 + 8 * kg);
          }
        }
        if (which == 0) {
          s = 0; ph = 0;
#pragma unroll 1
          for (int kg = 0; kg < 5; kg++) {
            const int grp = P.korder[kg];
            mbar_wait(dep3 + 8 * kg, 0);
            const CUtensorMap* mB = grp == 4 ? &P.mWo : &P.mWo2;
            const int p0 = grp == 4 ? 0 : 16 + grp * 16, r0 = grp == 4 ? 0 : grp * 1024;
#pragma unroll 1
            for (int ks = 0; ks < 16; ks++) {
              const uint32_t full = full3 + 8 * s, a = sbase + s * 32768;
              mbar_wait(empty3 + 8 * s, ph);
              if (elect_one()) {
                mbar_expect_tx(full, 32768);
                tma_load_3d(a, &P.mA3, 0, m3 * 128, p0 + ks, full);
                tma_load_3d_mc(a + 16384 + rank * 8192, mB, 0, r0 + ks * 64, n3 * 2 + rank, full, 3);
              }
              if (++s == ST3) { s = 0; ph ^= 1; }
            }
          }
        }
      }
    }
  } else {
    reg_alloc<240>();
    const bool lane0 = lane == 0;
    int nsig = 0;
    auto signal_done = [&]() { __syncwarp(); mbar_arrive_if(sig + 8 * (nsig & 7), lane0); nsig++; };
    {
      float acc[128];
      uint32_t pk[64];
      int s = s0, ph = 0;
      bf16* pend = nullptr;
      int code = 0, ncode = l1[0];
#pragma unroll
      for (int i = 0; i < 64; i++) pk[i] = 0;
      auto release = [&](int st) { if (lane < 2) mbar_arrive_cluster(empty1 + 8 * st, lane); };
      auto adv = [&]() { if (++s == ST1) { s = 0; ph ^= 1; } };
      uint32_t fr = 0;
      auto kstep = [&](int first) {
        if (!(first && fr)) mbar_wait(full1 + 8 * s, ph);
        const uint32_t a = sdesc + s * (STB1 >> 4);
        const uint32_t da = (a + wg * 512) | (1u << 16), db = (a + 1024) | (512u << 16);
        wg_fence();
#pragma unroll
        for (int k = 0; k < 4; k++) wgmma_ss_n256_a0b1(acc, desc64(da + k * 2, DHI_128), desc64(db + k * 128, DHI_128), (first && k == 0) ? 0 : 1);
        wg_commit();
      };
      auto store_part = [&](int i) {
        const int p = i >> 1, hh = i & 1;
        bf16* d = pend + (size_t)p * PANEL_ELEMS + hh * 8 * 64;
#pragma unroll
        for (int e = 0; e < 2; e++) {
          const int b = 2 * p + e;
          st_global_v4(d + e * 32, pk[(4 * b + 0) * 2 + hh], pk[(4 * b + 1) * 2 + hh], pk[(4 * b + 2) * 2 + hh], pk[(4 * b + 3) * 2 + hh]);
        }
      };
#pragma unroll 1
      for (int it = 0; ncode != 0xFFFF; it++) {
        const int nparts = it == 0 ? 0 : (code >> 9) == T_AKV ? 5 : 8;
        code = ncode;
        const int type = code >> 9, n = (code >> 4) & 31, m = code & 15;
        const int KS = (type == T_BK || type == T_BV) ? 8 : 16;
        int prev;
#pragma unroll
        for (int i = 0; i < 128; i++) asm volatile("" : "=f"(acc[i]));
        kstep(1); prev = s; adv();
        if (nparts) store_part(0);
#pragma unroll
        for (int ks = 1; ks < 8; ks++) {
          kstep(0);
          if (ks < nparts) store_part(ks);
          if (ks == 7 && nparts) signal_done();
          wg_wait<1>(); release(prev); prev = s; adv();
        }
#pragma unroll 1
        for (int ks = 8; ks < KS; ks++) {
          kstep(0); wg_wait<1>(); release(prev); prev = s; adv();
        }
        const int otid = opaque_tid();
        const int row = m * 128 + (otid >> 5) * 16 + ((otid >> 2) & 7);
        pend = (type == T_AQ ? g_a3 : g_qkv + (size_t)(type == T_AKV ? 192 : type * 64) * PANEL_ELEMS) + (size_t)(n * 4) * PANEL_ELEMS + (size_t)row * 64 + (otid & 3) * 8;
        ncode = l1[it + 1];
        fr = __shfl_sync(0xffffffffu, mbar_try(full1 + 8 * s + ((uint32_t)(uintptr_t)pend & P.zero), ph), 0) & (type < T_AQ);
        wg_wait<0>(); release(prev);
        fence_regs<128>(acc);
        if (type < T_AQ) {
#pragma unroll
          for (int i = 0; i < 64; i++) pk[i] = pack_bf16(acc[2 * i], acc[2 * i + 1]);
        } else {
          const uint32_t ex = sbase + s * STB1;
          uint32_t qf[64], phi[32];
          float pf[32];
          auto issue_fm = [&](uint32_t w) {
            wg_fence();
#pragma unroll
            for (int b = 0; b < 2; b++) {
              const uint64_t db = make_desc(w + b * 2048, 16, 512, 2);
              wgmma_rs_n32_b1(pf + 16 * b, qf + 8 * b, db, 0);
              wgmma_rs_n32_b1(pf + 16 * b, qf + 8 * b + 4, db + 64, 1);
            }
            wg_commit();
          };
#pragma unroll
          for (int i = 0; i < 64; i++) qf[i] = pack_bf16(acc[2 * i], acc[2 * i + 1]);
          mbar_wait(full1 + 8 * s, ph);
          issue_fm(ex);
          if (type == T_AKV) {
            const int srow = ((otid >> 5) & 3) * 16 + ((otid >> 3) & 1) * 8 + (otid & 7), scol = (otid >> 4) & 1;
            const int trow = wg * 64 + srow;
            const uint32_t vb = ex + 8192;
#pragma unroll
            for (int b = 0; b < 4; b++) {
#pragma unroll
              for (int j = 0; j < 4; j += 2)
                stmatrix_x4(vb + b * 10240 + (j + scol) * 2048 + trow * 16, qf[32 + 8 * b + 2 * j], qf[33 + 8 * b + 2 * j], qf[34 + 8 * b + 2 * j], qf[35 + 8 * b + 2 * j]);
            }
#pragma unroll
            for (int b = 0; b < 2; b++) st_shared_v4(vb + (2 * wg + b) * 10240 + 8192 + (otid & 127) * 16, 0x3F803F80u, 0x3F803F80u, 0x3F803F80u, 0x3F803F80u);
            wg_wait<0>(); fence_regs<32>(pf); fence_regs_u<32>(qf);
#pragma unroll
            for (int i = 0; i < 16; i++) qf[i] = qf[16 + i];
            float kv[20], kv0[20];
#pragma unroll
            for (int i = 0; i < 20; i++) kv[i] = 0.f;
#pragma unroll 1
            for (int r = 0; r < 2; r++) {
              hedgehog_phi(pf, phi);
              hedgehog_phi(pf + 16, phi + 16);
              mbar_arrive_if(sig, ((phi[7] | phi[15] | phi[23] | phi[31]) & P.zero) != 0);
              wg_wait<0>(); fence_regs<20>(kv);
#pragma unroll
              for (int i = 0; i < 20; i++) kv0[i] = kv[i];
              if (r) named_bar_sync(3, 256);
#pragma unroll
              for (int b = 0; b < 2; b++) {
#pragma unroll
                for (int j = 0; j < 8; j += 2)
                  stmatrix_x4(sQ0 + b * 16384 + trow * 128 + (((j + scol) ^ (srow & 7)) << 4), phi[16 * b + 2 * j], phi[16 * b + 2 * j + 1], phi[16 * b + 2 * j + 2], phi[16 * b + 2 * j + 3]);
              }
              fence_proxy_async_smem();
              named_bar_sync(3, 256);
              issue_fm(ex + 4096);
              const uint64_t da = make_desc(sQ0 + wg * 16384, 16, 1024, 1), dv = make_desc(vb + (2 * r + wg) * 10240, 128, 2048, 0);
              wg_fence();
#pragma unroll
              for (int k = 0; k < 8; k++) wgmma_ss_n40_a1b1(kv, da + k * 128, dv + k * 16, k > 0);
              wg_commit();
              wg_wait<1>(); fence_regs<32>(pf);
            }
            wg_wait<0>(); fence_regs<20>(kv);
#pragma unroll
            for (int i = 0; i < 64; i++) pk[i] = 0;
#pragma unroll
            for (int j = 0; j < 5; j++) {
#pragma unroll
              for (int c = 0; c < 4; c++) {
                pk[(4 * (2 * (j >> 1)) + c) * 2 + (j & 1)] = __float_as_uint(kv0[4 * j + c]);
                pk[(4 * (2 * (j >> 1) + 1) + c) * 2 + (j & 1)] = __float_as_uint(kv[4 * j + c]);
              }
            }
          } else {
            const int sw = s;
            adv();
            wg_wait<0>(); fence_regs<32>(pf); fence_regs_u<64>(qf);
            mbar_wait(full1 + 8 * s, ph);
            const uint32_t img = sbase + s * STB1;
            const float g0 = __ldcg(g_gate + row), g1 = __ldcg(g_gate + row + 8);
            float num[80];
#pragma unroll
            for (int i = 0; i < 80; i++) num[i] = 1.f;
            auto scale_o = [&](uint32_t* o  ) {
#pragma unroll
              for (int b = 0; b < 2; b++) {
                const float* np = num + 40 * b;
                const float* nm = np + 20;
                float a0 = rcp_approx(np[17]), b0 = rcp_approx(nm[17]), a1 = rcp_approx(np[19]), b1 = rcp_approx(nm[19]);
                const float t0 = g0 * rcp_approx(fmaf(np[16], a0, nm[16] * b0) + 1e-6f), t1 = g1 * rcp_approx(fmaf(np[18], a1, nm[18] * b1) + 1e-6f);
                a0 *= t0; b0 *= t0; a1 *= t1; b1 *= t1;
#pragma unroll
                for (int j = 0; j < 4; j++) {
                  o[8 * b + 2 * j] = pack_bf16(fmaf(np[4 * j], a0, nm[4 * j] * b0), fmaf(np[4 * j + 1], a0, nm[4 * j + 1] * b0));
                  o[8 * b + 2 * j + 1] = pack_bf16(fmaf(np[4 * j + 2], a1, nm[4 * j + 2] * b1), fmaf(np[4 * j + 3], a1, nm[4 * j + 3] * b1));
                }
              }
            };
#pragma unroll 1
            for (int r = 0; r < 4; r++) {
#pragma unroll
              for (int i = 0; i < 48; i++) qf[i] = qf[16 + i];
              hedgehog_exp(pf, phi);
              hedgehog_exp(pf + 16, phi + 16);
              scale_o(qf + 48);
              issue_fm(ex + ((r + 1) & 3) * 4096);
              wg_fence();
#pragma unroll
              for (int b = 0; b < 4; b++) {
                const uint64_t dk = make_desc(img + (2 * r + (b >> 1)) * 5120 + (b & 1) * 512, 128, 1024, 0);
                wgmma_rs_n40_b1(num + 20 * b, phi + 8 * b, dk, 0);
                wgmma_rs_n40_b1(num + 20 * b, phi + 8 * b + 4, dk + 16, 1);
              }
              wg_commit();
              wg_wait<0>(); fence_regs<80>(num); fence_regs<32>(pf); fence_regs_u<64>(qf);
            }
#pragma unroll
            for (int i = 0; i < 48; i++) pk[i] = qf[16 + i];
            scale_o(pk + 48);
            release(sw);
          }
          release(s); adv();
        }
      }
      {
        const int ot = opaque_tid();
        named_bar_sync(3, 256);
        const uint32_t stg = sbase + 3 * 32768 + wg * 32768;
        const uint32_t a = stg + (((ot >> 5) & 3) * 16 + ((ot >> 2) & 7)) * 128 + (ot & 3) * 16;
#pragma unroll
        for (int i = 0; i < 16; i++) {
          const int b = i >> 1, hh = i & 1, be = b ^ ((ot >> 2) & 1);
          const bool sw = (ot >> 2) & 1;
          const int b1 = b ^ 1;
          st_shared_v4(a + (be >> 1) * 8192 + (be & 1) * 64 + hh * 1024,
                       sw ? pk[(4 * b1 + 0) * 2 + hh] : pk[(4 * b + 0) * 2 + hh], sw ? pk[(4 * b1 + 1) * 2 + hh] : pk[(4 * b + 1) * 2 + hh],
                       sw ? pk[(4 * b1 + 2) * 2 + hh] : pk[(4 * b + 2) * 2 + hh], sw ? pk[(4 * b1 + 3) * 2 + hh] : pk[(4 * b + 3) * 2 + hh]);
        }
        fence_proxy_async_smem();
        asm volatile("st.shared.u64 [%0], %1;" :: "r"(lastdst + 8 * wg + (((ot & 127) == 0) ? 0 : 16)), "l"(pend) : "memory");
        signal_done();
      }
    }
    {
      float O[64], S[64];
      uint32_t PA[32], PB[32];
      float mc0 = 0.f, mc1 = 0.f, l0 = 1.f, l1s = 1.f, al0 = 1.f, al1 = 1.f, f0 = 1.f, f1 = 1.f, g0 = 0.f, g1 = 0.f;
      const uint32_t zero = P.zero;
      const uint32_t dq0 = (sdesc + 6 * 2048 + wg * 512) | (1u << 16), dk0 = sdesc | (1u << 16), dv0 = (sdesc + 2 * 2048) | (1024u << 16);
#pragma unroll
      for (int i = 0; i < 64; i++) O[i] = 0.f;
      auto final_scale = [&]() {
        float a = l0, b = l1s;
        a += __shfl_xor_sync(0xffffffffu, a, 1); b += __shfl_xor_sync(0xffffffffu, b, 1);
        a += __shfl_xor_sync(0xffffffffu, a, 2); b += __shfl_xor_sync(0xffffffffu, b, 2);
        f0 = (1.0f - g0) * rcp_approx(a); f1 = (1.0f - g1) * rcp_approx(b);
      };
      auto issue_qk = [&](uint32_t dq, uint32_t dk) {
        wg_fence();
#pragma unroll
        for (int k = 0; k < 8; k++)
          wgmma_ss_n128_a0b0(S, desc64(dq + (k >> 2) * 1024 + (k & 3) * 2, DHI_128), desc64(dk + (k >> 2) * 1024 + (k & 3) * 2, DHI_128), k > 0);
        wg_commit();
      };
      auto issue_pv = [&](const uint32_t* Pc, uint32_t dv) {
        wg_fence();
#pragma unroll
        for (int k = 0; k < 8; k++) wgmma_rs_n128_b1(O, Pc + 4 * k, desc64(dv + k * 128, DHI_128), 1);
        wg_commit();
      };
      uint32_t kr = 0, vr = 0, dep;
      float s0, s1;
      auto refresh_max = [&]() {
        float xa = fmaxf(S[0], S[1]), xb = fmaxf(S[4], S[5]), ya = fmaxf(S[2], S[3]), yb = fmaxf(S[6], S[7]);
#pragma unroll
        for (int j = 2; j < 16; j += 2) {
          xa = fmaxf(xa, fmaxf(S[4 * j], S[4 * j + 1])); xb = fmaxf(xb, fmaxf(S[4 * j + 4], S[4 * j + 5]));
          ya = fmaxf(ya, fmaxf(S[4 * j + 2], S[4 * j + 3])); yb = fmaxf(yb, fmaxf(S[4 * j + 6], S[4 * j + 7]));
        }
        float x0 = fmaxf(xa, xb), x1 = fmaxf(ya, yb);
        x0 = fmaxf(x0, __shfl_xor_sync(0xffffffffu, x0, 1)); x1 = fmaxf(x1, __shfl_xor_sync(0xffffffffu, x1, 1));
        x0 = fmaxf(x0, __shfl_xor_sync(0xffffffffu, x0, 2)); x1 = fmaxf(x1, __shfl_xor_sync(0xffffffffu, x1, 2));
        x0 = fmaxf(x0 * SM_SCALE, mc0); x1 = fmaxf(x1 * SM_SCALE, mc1);
        al0 = ex2(mc0 - x0); al1 = ex2(mc1 - x1);
        mc0 = x0; mc1 = x1;
        l0 *= al0; l1s *= al1;
      };
      auto exps = [&](uint32_t* Pn, const int j0, const int j1, auto with_store, bf16* dst, const uint32_t* T) {
        if (j0 == 0) { s0 = 0.f; s1 = 0.f; }
#pragma unroll
        for (int j = j0; j < j1; j++) {
          const float e0 = ex2(fmaf(S[4 * j], SM_SCALE, -mc0)), e1 = ex2(fmaf(S[4 * j + 1], SM_SCALE, -mc0));
          const float e2 = ex2(fmaf(S[4 * j + 2], SM_SCALE, -mc1)), e3 = ex2(fmaf(S[4 * j + 3], SM_SCALE, -mc1));
          s0 += e0 + e1; s1 += e2 + e3;
          Pn[2 * j] = pack_bf16(e0, e1); Pn[2 * j + 1] = pack_bf16(e2, e3);
          if (j == 12) dep = (__float_as_uint(s0) | __float_as_uint(s1)) & zero;
          if (decltype(with_store)::value) {
            const int i = j - 8, b = i >> 1;
            bf16* d = dst + (size_t)(b >> 1) * PANEL_ELEMS + (b & 1) * 32 + (i & 1) * 8 * 64 + (__float_as_uint(s1) & zero);
            if (dst) st_global_v4(d, T[4 * i], T[4 * i + 1], T[4 * i + 2], T[4 * i + 3]);
          }
        }
      };
      auto finish_pack = [&](uint32_t* T) {
#pragma unroll
        for (int b = 0; b < 4; b++) {
#pragma unroll
          for (int j = 0; j < 4; j++) {
            T[8 * b + j] = pack_bf16(O[16 * b + 4 * j] * f0, O[16 * b + 4 * j + 1] * f0);
            T[8 * b + 4 + j] = pack_bf16(O[16 * b + 4 * j + 2] * f1, O[16 * b + 4 * j + 3] * f1);
          }
        }
      };
      int qs = 1, qph = 1, ks = 0, kph = 0, vs = 0, vph = 0;
      bf16* optr = nullptr;
      int prow = 0;
#pragma unroll
      for (int i = 0; i < 32; i++) { PA[i] = 0; PB[i] = 0; }
      uint32_t dkc = dk0, dvc = dv0;
      auto adv_k = [&]() { ks ^= 1; kph ^= (ks == 0); dkc = 2 * dk0 + 2048 - dkc; };
      auto adv_v = [&]() { if (++vs == VST) { vs = 0; vph ^= 1; } dvc += 2048; if (dvc == dv0 + VST * 2048) dvc = dv0; };
      uint32_t qr = 0, cslot = scode;
      int ncode = 0;
      auto peek_item = [&]() {
        qr = mbar_try(qfull + 8 * (qs ^ 1), qph ^ qs);
        asm volatile("ld.shared.u32 %0, [%1];" : "=r"(ncode) : "r"(cslot) : "memory");
      };
      bool flip = false;
      bool any = false;
      auto unflip = [&]() {
        if (flip) {
#pragma unroll
          for (int i = 0; i < 32; i++) asm volatile("mov.b32 %0, %1;" : "=r"(PA[i]) : "r"(PB[i]));
        }
      };
      auto hot = [&](uint32_t* Pc, uint32_t* Pn, bool lastq) {
        if (UNLIKELY(!(kr & vr))) { mbar_wait(vfull + 8 * vs, vph); mbar_wait(kfull + 8 * ks, kph); }
        named_bar_sync(1 + wg, 256);
        issue_qk(dq0 - qs * 2048, dkc);
        issue_pv(Pc, dvc);
        named_bar_arrive(2 - wg, 256);
        const uint32_t vrel = vempty + 8 * vs;
        adv_v();
        wg_wait<1>(); fence_regs<64>(S);
        mc1 = __uint_as_float(__float_as_uint(mc1) | (mbar_arrive_if_dep(kempty + 8 * ks, lane0) & zero));
        mbar_arrive_if(qempty + 8 * qs, lane0 && lastq);
        adv_k();
        exps(Pn, 0, 16, BoolTag<false>(), nullptr, nullptr);
        kr = mbar_try(kfull + 8 * ks + dep, kph);
        vr = mbar_try(vfull + 8 * vs, vph);
        peek_item();
        const bool redo = __any_sync(0xffffffffu, fmaxf(s0, s1) > 1.0995116e12f);
        wg_wait<0>(); fence_regs<64>(O); fence_regs_u<32>(Pc);
        mbar_arrive_if(vrel, lane0);
        if (UNLIKELY(redo)) {
          refresh_max();
#pragma unroll
          for (int j = 0; j < 16; j++) { O[4 * j] *= al0; O[4 * j + 1] *= al0; O[4 * j + 2] *= al1; O[4 * j + 3] *= al1; }
          exps(Pn, 0, 16, BoolTag<false>(), nullptr, nullptr);
        }
        l0 += s0; l1s += s1;
      };
      if (wg == 1) named_bar_arrive(1, 256);
#pragma unroll 1
      for (int it = 0;; it++) {
        qs ^= 1; qph ^= (qs == 0);
        if (!qr) {
          mbar_wait(qfull + 8 * qs, qph);
          asm volatile("ld.shared.u32 %0, [%1];" : "=r"(ncode) : "r"(cslot) : "memory");
        }
        const int code = __shfl_sync(0xffffffffu, ncode, 0);
        cslot = scode + 4 * ((it + 1) & 7);
        if (code == 0xFFFF) break;
        const int n = (code & 15) + 1;
        {
          if (!(kr & vr)) { if (it > 0) mbar_wait(vfull + 8 * vs, vph); mbar_wait(kfull + 8 * ks, kph); }
          named_bar_sync(1 + wg, 256);
          issue_qk(dq0 - qs * 2048, dkc);
          const int ot = opaque_tid();
          const int rloc = (ot >> 5) * 16 + ((ot >> 2) & 7);
          g0 = __ldcg(g_gate + prow + rloc); g1 = __ldcg(g_gate + prow + rloc + 8);
          unflip();
          if (it > 0) issue_pv(PA, dvc); else wg_commit();
          named_bar_arrive(2 - wg, 256);
          wg_wait<1>(); fence_regs<64>(S);
          mbar_arrive_if(kempty + 8 * ks, lane0);
          adv_k();
          final_scale();
          const int th = rloc - 2 * (ot & 3);
#pragma unroll
          for (int j = 0; j < 16; j++) {
            if (8 * j > th) S[4 * j] = -INFINITY;
            if (8 * j + 1 > th) S[4 * j + 1] = -INFINITY;
            if (8 * j - 8 > th) S[4 * j + 2] = -INFINITY;
            if (8 * j - 7 > th) S[4 * j + 3] = -INFINITY;
          }
          mc0 = __shfl_sync(0xffffffffu, S[0] * SM_SCALE, lane & 28);
          mc1 = __shfl_sync(0xffffffffu, S[2] * SM_SCALE, lane & 28);
          exps(PB, 0, 8, BoolTag<false>(), nullptr, nullptr);
          mbar_arrive_if(qempty + 8 * qs + ((__float_as_uint(s0) | __float_as_uint(s1)) & zero), lane0 && n == 1);
          wg_wait<0>(); fence_regs<64>(O); fence_regs_u<32>(PA);
          mbar_arrive_if(vempty + 8 * vs, lane0 && it > 0);
          if (it > 0) adv_v();
          finish_pack(PA);
#pragma unroll
          for (int i = 0; i < 64; i++) O[i] = 0.f;
          exps(PB, 8, 16, BoolTag<true>(), optr, PA);
          kr = mbar_try(kfull + 8 * ks + dep, kph);
          vr = mbar_try(vfull + 8 * vs, vph);
          peek_item();
          prow = (code & 15) * 128;
          optr = g_a3 + (size_t)(16 + 2 * (code >> 4)) * PANEL_ELEMS + (size_t)(prow + rloc) * 64 + (ot & 3) * 8;
          __syncwarp(); mbar_arrive_if(sig + 8 * (nsig & 7), lane0 && it > 0); nsig += it > 0;
          if (UNLIKELY(__any_sync(0xffffffffu, fmaxf(s0, s1) > 1.0995116e12f))) { refresh_max(); exps(PB, 0, 16, BoolTag<false>(), nullptr, nullptr); }
          l0 = s0; l1s = s1;
        }
#pragma unroll 1
        for (int t = 1; t < n; t += 2) {
          hot(PB, PA, t == n - 1);
          if (t < n - 1) hot(PA, PB, t == n - 2);
        }
        flip = n & 1;
        any = true;
      }
      if (any) {
        const int ot = opaque_tid();
        g0 = __ldcg(g_gate + prow + (ot >> 5) * 16 + ((ot >> 2) & 7)); g1 = __ldcg(g_gate + prow + (ot >> 5) * 16 + ((ot >> 2) & 7) + 8);
        unflip();
        if (!vr) mbar_wait(vfull + 8 * vs, vph);
        named_bar_sync(1 + wg, 256);
        issue_pv(PA, dvc);
        if (wg == 0) named_bar_arrive(2, 256);
        final_scale();
        wg_wait<0>(); fence_regs<64>(O); fence_regs_u<32>(PA);
        mbar_arrive_if(vempty + 8 * vs, lane0);
        finish_pack(PB);
#pragma unroll
        for (int i = 0; i < 8; i++)
          st_global_v4(optr + (size_t)(i >> 2) * PANEL_ELEMS + ((i >> 1) & 1) * 32 + (i & 1) * 8 * 64, PB[4 * i], PB[4 * i + 1], PB[4 * i + 2], PB[4 * i + 3]);
        signal_done();
      }
    }
    const int t3 = P.t3[cta], m3 = t3 & 15, n3 = t3 >> 4;
    if (t3 != 0xFFFF) {
      float acc[64];
      int s = 0, ph = 0, prev = 0;
      mbar_wait(go3, 0);
#pragma unroll 1
      for (int ks = 0; ks < 80; ks++) {
        mbar_wait(full3 + 8 * s, ph);
        const uint32_t a = sdesc + s * 2048;
        const uint32_t da = (a + wg * 512) | (1u << 16), db = (a + 1024) | (512u << 16);
        wg_fence();
#pragma unroll
        for (int k = 0; k < 4; k++) wgmma_ss_n128_a0b1(acc, desc64(da + k * 2, DHI_128), desc64(db + k * 128, DHI_128), (ks == 0 && k == 0) ? 0 : 1);
        wg_commit();
        wg_wait<1>();
        if (ks > 0 && ks <= 80 - ST3 && lane0) { mbar_arrive_cluster(empty3 + 8 * prev, 0); mbar_arrive_cluster(empty3 + 8 * prev, 1); }
        prev = s;
        if (++s == ST3) { s = 0; ph ^= 1; }
      }
      wg_wait<0>();
      fence_regs<64>(acc);
      const uint32_t mystg = sQ0 + wg * 16384;
      const int srow = (warp & 3) * 16 + ((lane >> 3) & 1) * 8 + (lane & 7), scol = lane >> 4;
#pragma unroll
      for (int j = 0; j < 16; j += 2) {
        const int p = j >> 3, c = (j & 7) + scol;
        stmatrix_x4(mystg + p * 8192 + srow * 128 + ((c ^ (srow & 7)) << 4),
                    pack_bf16(acc[4 * j], acc[4 * j + 1]), pack_bf16(acc[4 * j + 2], acc[4 * j + 3]),
                    pack_bf16(acc[4 * j + 4], acc[4 * j + 5]), pack_bf16(acc[4 * j + 6], acc[4 * j + 7]));
      }
      fence_proxy_async_smem();
      named_bar_sync(6 + wg, 128);
      if ((tid & 127) == 0) {
        tma_store_2d(&P.mOut, mystg, n3 * 128, m3 * 128 + wg * 64);
        tma_store_2d(&P.mOut, mystg + 8192, n3 * 128 + 64, m3 * 128 + wg * 64);
        bulk_commit();
        if (t3 == 0 && wg == 0) g_epoch = __ldcg(&g_epoch) + 1;
        asm volatile("cp.async.bulk.wait_group.read 0;" ::: "memory");
      }
    }
  }
}

typedef CUresult (*PFN_encodeTiled)(CUtensorMap*, CUtensorMapDataType, cuuint32_t, void*, const cuuint64_t*, const cuuint64_t*,
                                    const cuuint32_t*, const cuuint32_t*, CUtensorMapInterleave, CUtensorMapSwizzle,
                                    CUtensorMapL2promotion, CUtensorMapFloatOOBfill);
static PFN_encodeTiled g_encode = nullptr;
static void make_map(CUtensorMap* m, const void* ptr, int rank, uint64_t d0, uint64_t d1, uint64_t d2, uint64_t s1, uint64_t s2,
                     uint32_t b0, uint32_t b1, uint32_t b2, CUtensorMapSwizzle swz) {
  cuuint64_t d[3] = {d0, d1, d2}, s[2] = {s1, s2};
  cuuint32_t b[3] = {b0, b1, b2}, es[3] = {1, 1, 1};
  g_encode(m, CU_TENSOR_MAP_DATA_TYPE_BFLOAT16, rank, (void*)ptr, d, s, b, es, CU_TENSOR_MAP_INTERLEAVE_NONE, swz,
           CU_TENSOR_MAP_L2_PROMOTION_L2_256B, CU_TENSOR_MAP_FLOAT_OOB_FILL_NONE);
}

static int pair_class(int p) {
  const int t = (p + 62) % 66;
  if (t < 32) return t & 7;
  if (t < 60) return 1 + (t - 32) % 7;
  return t < 62 ? 8 : 0;
}
static void list_schedule(const uint16_t* codes, const float* cost, int njobs, int maxper, uint16_t* lists, float* load) {
  int cnt[66];
  for (int i = 0; i < 66; i++) cnt[i] = 0;
  for (int i = 0; i < 66 * maxper; i++) lists[i] = 0xFFFF;
  for (int j = 0; j < njobs; j++) {
    int best = -1;
    for (int i = 0; i < 66; i++) if (cnt[i] < maxper - 2 && (pair_class(i) == 8 ? (codes[j] >> 9) != T_AKV : pair_class(i) == ((codes[j] & 15) >> 1)) && (best < 0 || load[i] < load[best] - 1e-4f)) best = i;
    lists[best * maxper + cnt[best]++] = codes[j];
    load[best] += cost[j];
  }
}

static Params g_p;
static const void* g_last_in[11];
static void* g_last_out = nullptr;
static bool g_setup_done = false;
constexpr int HSHIFT = 2, SHORT_CUT = 8, AQ_POS = 16, GORDER = 0x2310;
constexpr float AKV_COST = 22.0f, AQ_COST = 24.0f;

extern "C" void kernel_launch(void* const* d_in, const int* in_sizes, int n_in, void* d_out, int out_size) {
  bool same = g_setup_done && g_last_out == d_out;
  for (int i = 0; i < 11 && same; i++) same = g_last_in[i] == d_in[i];
  if (!same) {
    if (!g_encode) {
      cudaDriverEntryPointQueryResult qr; void* p = nullptr;
      cudaGetDriverEntryPoint("cuTensorMapEncodeTiled", &p, cudaEnableDefault, &qr);
      g_encode = (PFN_encodeTiled)p;
    }
    void *p_qkv, *p_a3;
    cudaGetSymbolAddress(&p_qkv, g_qkv); cudaGetSymbolAddress(&p_a3, g_a3);
    const CUtensorMapSwizzle S128 = CU_TENSOR_MAP_SWIZZLE_128B;
    make_map(&g_p.mX, d_in[0], 2, 1024, 2048, 1, 2048, 0, 64, 128, 1, S128);
    make_map(&g_p.mC, d_in[5], 2, 512, 2048, 1, 1024, 0, 64, 128, 1, S128);
    make_map(&g_p.mW[3], d_in[1], 3, 64, 1024, 48, 3072 * 2, 128, 64, 64, 2, S128);
    make_map(&g_p.mW[0], d_in[6], 3, 64, 1024, 64, 4096 * 2, 128, 64, 64, 2, S128);
    make_map(&g_p.mW[1], d_in[7], 3, 64, 512, 64, 4096 * 2, 128, 64, 64, 2, S128);
    make_map(&g_p.mW[2], d_in[8], 3, 64, 512, 64, 4096 * 2, 128, 64, 64, 2, S128);
    make_map(&g_p.mQKV, p_qkv, 3, 64, 2048, 192, 128, (uint64_t)PANEL_ELEMS * 2, 64, 128, 2, S128);
    make_map(&g_p.mA3, p_a3, 3, 64, 2048, 80, 128, (uint64_t)PANEL_ELEMS * 2, 64, 128, 1, S128);
    make_map(&g_p.mWo, d_in[3], 3, 64, 1024, 16, 1024 * 2, 128, 64, 64, 1, S128);
    make_map(&g_p.mWo2, d_in[9], 3, 64, 4096, 16, 1024 * 2, 128, 64, 64, 1, S128);
    make_map(&g_p.mOut, d_out, 2, 1024, 2048, 1, 2048, 0, 64, 64, 1, S128);
    make_map(&g_p.mWphi, d_in[2], 2, 32, 1024, 1, 64, 0, 32, 128, 1, CU_TENSOR_MAP_SWIZZLE_64B);
    g_p.x = (const bf16*)d_in[0]; g_p.gate_w = (const bf16*)d_in[10];
    g_p.zero = 0;
    float load[132];
    for (int i = 0; i < 132; i++) load[i] = 0.f;
    {
      static uint16_t codes[480], pl[66 * MAXT1]; static float cost[480]; int nj = 0;
      auto add = [&](int type, int n, float c) { for (int m = 0; m < 16; m += 2) { codes[nj] = (uint16_t)((type << 9) | (n << 4) | m); cost[nj++] = c; } };
      for (int n = 0; n <= 16; n++) {
        if (n == 0) for (int a = 0; a < 8; a++) add(T_AKV, a, AKV_COST);
        if (n == AQ_POS) for (int a = 0; a < 4; a++) add(T_AQ, a, AQ_COST);
        if (n < 16) { add(T_BQ, n, 16.5f); add(T_BK, n, 8.5f); add(T_BV, n, 8.5f); }
      }
      list_schedule(codes, cost, nj, MAXT1, pl, load);
      for (int c = 0; c < 132; c++)
        for (int i = 0; i < MAXT1; i++) g_p.l1[c][i] = pl[(c >> 1) * MAXT1 + i] | (uint16_t)(c & 1);
      for (int c = 0; c < 132; c++) {
        int extra = 0;
        for (int i = 0; g_p.l1[c][i] != 0xFFFF; i++) { const int ty = g_p.l1[c][i] >> 9; extra += ty == T_AKV ? 1 : ty == T_AQ ? 2 : 0; }
        g_p.l1[c][MAXT1 - 1] = (uint16_t)((8 - extra) & 3);
      }
    }
    const int gorder[4] = {(GORDER >> 12) & 3, (GORDER >> 8) & 3, (GORDER >> 4) & 3, GORDER & 3};
    {
      int nj = 0;
      uint16_t all[512];
      int na = 0;
      for (int gi = 0; gi < 2; gi++)
        for (int qt = 15; qt >= SHORT_CUT; qt--)
          for (int h = gorder[gi] * 8; h < gorder[gi] * 8 + 8; h++) all[na++] = (uint16_t)((((h + 32 - HSHIFT) & 31) << 4) | qt);
      for (int qt = 15; qt >= 0; qt--)
        for (int gi = (qt >= SHORT_CUT ? 2 : 0); gi < 4; gi++)
          for (int h = gorder[gi] * 8; h < gorder[gi] * 8 + 8; h++) all[na++] = (uint16_t)((((h + 32 - HSHIFT) & 31) << 4) | qt);
      auto shared_item = [&](uint16_t c) { return (c & 15) < OWN_CUT || (((((c >> 4) + HSHIFT) & 31) >> 3) == gorder[0] && (c & 15) == 12); };
      for (int k = 0; k < 8; k++)
        for (int i = 0; i < 512; i++) if (!shared_item(all[i]) && ((all[i] >> 4) & 7) == k) g_p.items[nj++] = all[i];
      for (int i = 0; i < 512; i++) if (shared_item(all[i])) g_p.items[nj++] = all[i];
      while (nj < 520) g_p.items[nj++] = 0xFFFF;
    }
    {
      int cnt[9] = {0, 0, 0, 0, 0, 0, 0, 0, 0};
      for (int p = 0; p < 66; p++) {
        const int k = pair_class(p), n = cnt[k]++;
        for (int r = 0; r < 2; r++) g_p.t3[2 * p + r] = k < 8 ? (uint16_t)((n << 4) | (k * 2 + r)) : (uint16_t)0xFFFF;
      }
    }
    g_p.korder[0] = 4;
    for (int gi = 0; gi < 4; gi++) g_p.korder[1 + gi] = gorder[gi];
    cudaFuncSetAttribute(fused_kernel, cudaFuncAttributeMaxDynamicSharedMemorySize, SMEM_BYTES);
    for (int i = 0; i < 11; i++) g_last_in[i] = d_in[i];
    g_last_out = d_out;
    g_setup_done = true;
  }
  fused_kernel<<<132, 384, SMEM_BYTES>>>(g_p);
}
```
